```python
import torch

def _softmax(x, axis=-1):
    return torch.softmax(x, dim=axis)
def _gelu(x):
    return torch.nn.functional.gelu(x, approximate="tanh")
def _silu(x):
    return torch.nn.functional.silu(x)
def _sigmoid(x):
    return torch.sigmoid(x)
def _layernorm(x, axis=-1, eps=1e-5):
    m = x.mean(dim=axis, keepdim=True)
    v = x.var(dim=axis, keepdim=True, unbiased=False)
    return (x - m) / torch.sqrt(v + eps)
def _scatter_add(tgt, idx, src, axis=0):
    return tgt.clone().index_add_(axis, idx, src)
def _segment_sum(src, seg, n):
    out = torch.zeros((n,) + src.shape[1:], dtype=src.dtype)
    return out.index_add_(0, seg, src)
def _pad(x, pw):
    flat = tuple(v for pair in reversed(pw) for v in pair)
    return torch.nn.functional.pad(x, flat)

kernel_name = 'sequential_preLN__sliding_block_cached__glu_gated_bilinear__decode'

def setup_inputs():

    _w = (lambda a: (lambda t: t.to(torch.bfloat16) if t.is_floating_point() else t)(torch.as_tensor(a)))
    def _A_setup():
        B, Sq, D = 1, 1, 448
        Hq, Hkv, Sk, Dh = 16, 8, 65536, 256
        assert Hq % Hkv == 0, (Hq, Hkv)
        return {
            "x": _w((lambda *s: torch.randn(*s, dtype=torch.bfloat16) * 0.05)(B, Sq, D)),
            "k_cache": _w((lambda *s: torch.randn(*s, dtype=torch.bfloat16) * 1.6)(B, Hkv, Sk, Dh)),
            "v_cache": _w((lambda *s: torch.randn(*s, dtype=torch.bfloat16) * 0.8)(B, Hkv, Sk, Dh)),
            "wq": _w((lambda *s: torch.randn(*s, dtype=torch.bfloat16) * 1.6)(D, Hq * Dh) * (D ** -0.5)),
            "wo": _w((lambda *s: torch.randn(*s, dtype=torch.bfloat16) * 0.8)(Hq * Dh, D) * ((Hq * Dh) ** -0.5)),
        }
    _A_in = _A_setup()

    def _B_setup():
        B, S, D, F = 1, 1, 448, 1792
        return {
            "x": _w((lambda *s: torch.randn(*s, dtype=torch.bfloat16) * 0.05)(B, S, D)),
            "w_gate": _w((lambda *s: torch.randn(*s, dtype=torch.bfloat16) * 0.4)(D, F) * (D ** -0.5)),
            "w_up": _w((lambda *s: torch.randn(*s, dtype=torch.bfloat16) * 0.4)(D, F) * (D ** -0.5)),
            "w_down": _w((lambda *s: torch.randn(*s, dtype=torch.bfloat16) * 0.4)(F, D) * (F ** -0.5)),
        }
    _B_in = _B_setup()

    return {
        "A_x": _A_in["x"],
        "A_k_cache": _A_in["k_cache"],
        "A_v_cache": _A_in["v_cache"],
        "A_wq": _A_in["wq"],
        "A_wo": _A_in["wo"],
        "B_x": _B_in["x"],
        "B_w_gate": _B_in["w_gate"],
        "B_w_up": _B_in["w_up"],
        "B_w_down": _B_in["w_down"],
    }

def reference(A_x, A_k_cache, A_v_cache, A_wq, A_wo, B_x, B_w_gate, B_w_up, B_w_down):
    def _A_ref(x, k_cache, v_cache, wq, wo):
        B, Sq, D = x.shape
        Hq, Dh = 16, 256
        Hkv, Sk = k_cache.shape[1], k_cache.shape[2]
        W = min(4096, max(256, Sk // 4))
        rep = Hq // Hkv
        q = (lambda x, *d: x.permute(*d))((x @ wq).reshape(B, Sq, Hq, Dh), 0, 2, 1, 3)
        k = (lambda x, n, axis: torch.repeat_interleave(x, n, dim=axis))(k_cache[:, :, Sk - W:, :], rep, axis=1)
        v = (lambda x, n, axis: torch.repeat_interleave(x, n, dim=axis))(v_cache[:, :, Sk - W:, :], rep, axis=1)
        scores = torch.einsum("bhqd,bhkd->bhqk", q, k) * (Dh ** -0.5)
        p = _softmax(scores, axis=-1)
        o = torch.einsum("bhqk,bhkd->bhqd", p, v)
        return (lambda x, *d: x.permute(*d))(o, 0, 2, 1, 3).reshape(B, Sq, Hq * Dh) @ wo

    def _B_ref(x, w_gate, w_up, w_down):
        g = torch.einsum("bsd,df->bsf", x, w_gate)
        u = torch.einsum("bsd,df->bsf", x, w_up)
        h = g * u
        return torch.einsum("bsf,fd->bsd", h, w_down)

    x = A_x
    h = x + _A_ref(_layernorm(x, axis=-1), A_k_cache, A_v_cache, A_wq, A_wo)
    h2 = h + _B_ref(_layernorm(h, axis=-1), B_w_gate, B_w_up, B_w_down)
    return h2
```

```cpp
#include <cuda_runtime.h>
#include <cuda_bf16.h>
#include <cuda.h>
#include <stdint.h>
#include <stddef.h>

namespace {

constexpr int DM = 448, SK = 65536, WIN = 4096, FF = 1792;
constexpr int NCTA = 128, NFFN = 56;
constexpr int NTHREADS = 320;
constexpr int UNIT = 8192;
constexpr int SPIN_LIMIT = 1 << 20;

#define PFMAP 0
#define NREP 2
#define WMAX 8
#define DT_NS 344
#define PSTART 3
#define SSTART (PSTART + 1)
#define HSTART 2
#define PSLEEP 200
#define OSTART 14
#define STAG 0
#define ODIRECT 0
#define WARM 7
#define O_D 0
#define H_D 0
#define NPW 0
#define HTRY 200
#define P2_D 1500
#define WO_B 26
#define WO_N 4
#define WO_T0 11200
#define WO_DT 148
#define GU_T0 12700
#define GU_B 29
#define GU_D0 200
#define GU_DT 260
#define T0_NS 200

constexpr int NUNIT = 27;
constexpr int SM_WQ = 23 * UNIT;
constexpr int SM_WO = 5 * UNIT;
constexpr int SM_OB = 13 * UNIT;
constexpr int SM_GU = 5 * UNIT;
constexpr int SM_DN = SM_GU + 57344;
constexpr int SM_G1 = NUNIT * UNIT;
constexpr int SM_RED = SM_G1 + 4096;
constexpr int SM_Q = SM_RED + 2048;
constexpr int SM_XN = SM_Q + 1024;
constexpr int SM_SC = SM_XN + 1024;
constexpr int SM_BAR = SM_SC + 1024;
constexpr int SM_TOTAL = SM_BAR + 42 * 8;
static_assert(SM_TOTAL <= 232448, "smem");

enum { BAR_K = 0, BAR_V = 16, BAR_W = 32, BAR_DN = 36, BAR_WQ = 40, BAR_K_FREE = 41 };
enum { NB_PV = 1, NB_G1 = 2, NB_Q = 3, NB_INIT = 4, NB_SC = 5, NB_WO = 6, NB_O = 7, NB_S = 8, NB_H = 9, NB_G2 = 10 };

struct __align__(128) Scratch {
    uint32_t q[8][256];
    uint32_t e[8][128][32];
    uint32_t st[8][128][8];
    uint32_t ob[NCTA][32];
    uint32_t pb[NREP][4][DM];
    uint32_t p2[56][NFFN][8];
};
constexpr int OQ = offsetof(Scratch, q), OE = offsetof(Scratch, e), OST = offsetof(Scratch, st), OOB = offsetof(Scratch, ob),
              OPB = offsetof(Scratch, pb), OP2 = offsetof(Scratch, p2);
__device__ Scratch g_scr[2];
__device__ uint32_t g_epoch;

struct Maps {
    CUtensorMap m[6];
};

#define TL(i) do {} while (0)

#define TL0(i) do {} while (0)
__device__ __forceinline__ void mbar_init(uint32_t bar, int cnt) { asm volatile("mbarrier.init.shared::cta.b64 [%0], %1;" :: "r"(bar), "r"(cnt) : "memory"); }
__device__ __forceinline__ void mbar_expect_tx(uint32_t bar, uint32_t bytes) { asm volatile("mbarrier.arrive.expect_tx.shared::cta.b64 _, [%0], %1;" :: "r"(bar), "r"(bytes) : "memory"); }
__device__ __forceinline__ void mbar_arrive(uint32_t bar) { asm volatile("mbarrier.arrive.shared::cta.b64 _, [%0];" :: "r"(bar) : "memory"); }
__device__ __forceinline__ bool mbar_test(uint32_t bar) {
    uint32_t ok;
    asm volatile("{\n.reg .pred p;\nmbarrier.test_wait.parity.shared::cta.b64 p, [%1], 0;\nselp.u32 %0, 1, 0, p;\n}" : "=r"(ok) : "r"(bar) : "memory");
    return ok;
}
__device__ __forceinline__ bool mbar_try(uint32_t bar, uint32_t ns) {
    uint32_t ok;
    asm volatile("{\n.reg .pred p;\nmbarrier.try_wait.parity.shared::cta.b64 p, [%1], 0, %2;\nselp.u32 %0, 1, 0, p;\n}" : "=r"(ok) : "r"(bar), "r"(ns) : "memory");
    return ok;
}
__device__ __forceinline__ void mbar_wait(uint32_t bar) {
    asm volatile("{\n.reg .pred p;\nW_%=:\nmbarrier.try_wait.parity.shared::cta.b64 p, [%0], 0;\n@!p bra W_%=;\n}" :: "r"(bar) : "memory");
}
__device__ __forceinline__ uint32_t gtime32() { uint32_t t; asm volatile("mov.u32 %0, %%globaltimer_lo;" : "=r"(t) :: "memory"); return t; }
__device__ __forceinline__ void tma3d(uint32_t dst, const CUtensorMap* tm, int c0, int c1, uint32_t bar) {
    asm volatile("cp.async.bulk.tensor.3d.shared::cluster.global.mbarrier::complete_tx::bytes [%0], [%1, {%3, %4, %5}], [%2];" :: "r"(dst), "l"(tm), "r"(bar), "r"(c0), "r"(c1), "r"(0) : "memory");
}
template <int DO, int SO> __device__ __forceinline__ void cp_async16(uint32_t dst, const void* src) { asm volatile("cp.async.cg.shared.global.L2::128B [%0+%2], [%1+%3], 16;" :: "r"(dst), "l"(src), "n"(DO), "n"(SO) : "memory"); }
__device__ __forceinline__ void nb_sync(int id, int n) { asm volatile("bar.sync %0, %1;" :: "r"(id), "r"(n) : "memory"); }
__device__ __forceinline__ void nb_arrive(int id, int n) { asm volatile("bar.arrive %0, %1;" :: "r"(id), "r"(n) : "memory"); }
__device__ __forceinline__ void ldsm4t(uint32_t (&r)[4], uint32_t addr) {
    asm volatile("ldmatrix.sync.aligned.m8n8.x4.trans.shared.b16 {%0,%1,%2,%3}, [%4];" : "=r"(r[0]), "=r"(r[1]), "=r"(r[2]), "=r"(r[3]) : "r"(addr) : "memory");
}
__device__ __forceinline__ void mma16816(float (&c)[4], uint32_t a0, uint32_t a1, uint32_t a2, uint32_t a3, uint32_t b0, uint32_t b1) {
    asm volatile("mma.sync.aligned.m16n8k16.row.col.f32.bf16.bf16.f32 {%0,%1,%2,%3}, {%4,%5,%6,%7}, {%8,%9}, {%0,%1,%2,%3};"
                 : "+f"(c[0]), "+f"(c[1]), "+f"(c[2]), "+f"(c[3]) : "r"(a0), "r"(a1), "r"(a2), "r"(a3), "r"(b0), "r"(b1));
}
__device__ __forceinline__ void mma16816(float (&c)[4], const uint32_t (&a)[4], uint32_t b0, uint32_t b1) { mma16816(c, a[0], a[1], a[2], a[3], b0, b1); }
__device__ __forceinline__ void mma16816z(float (&c)[4], const uint32_t (&a)[4], uint32_t b0, uint32_t b1) {
    asm volatile("mma.sync.aligned.m16n8k16.row.col.f32.bf16.bf16.f32 {%0,%1,%2,%3}, {%4,%5,%6,%7}, {%8,%9}, {%10,%10,%10,%10};"
                 : "=f"(c[0]), "=f"(c[1]), "=f"(c[2]), "=f"(c[3]) : "r"(a[0]), "r"(a[1]), "r"(a[2]), "r"(a[3]), "r"(b0), "r"(b1), "f"(0.f));
}
__device__ __forceinline__ uint4 lds128(uint32_t a) { uint4 v; asm volatile("ld.shared.v4.b32 {%0,%1,%2,%3}, [%4];" : "=r"(v.x), "=r"(v.y), "=r"(v.z), "=r"(v.w) : "r"(a) : "memory"); return v; }
__device__ __forceinline__ float4 lds128f(uint32_t a) { float4 v; asm volatile("ld.shared.v4.f32 {%0,%1,%2,%3}, [%4];" : "=f"(v.x), "=f"(v.y), "=f"(v.z), "=f"(v.w) : "r"(a) : "memory"); return v; }
__device__ __forceinline__ uint2 lds64(uint32_t a) { uint2 v; asm volatile("ld.shared.v2.b32 {%0,%1}, [%2];" : "=r"(v.x), "=r"(v.y) : "r"(a) : "memory"); return v; }
__device__ __forceinline__ float2 lds64f(uint32_t a) { float2 v; asm volatile("ld.shared.v2.f32 {%0,%1}, [%2];" : "=f"(v.x), "=f"(v.y) : "r"(a) : "memory"); return v; }
__device__ __forceinline__ float lds32f(uint32_t a) { float v; asm volatile("ld.shared.f32 %0, [%1];" : "=f"(v) : "r"(a) : "memory"); return v; }
__device__ __forceinline__ void sts128(uint32_t a, uint32_t x, uint32_t y, uint32_t z, uint32_t w) { asm volatile("st.shared.v4.b32 [%0], {%1,%2,%3,%4};" :: "r"(a), "r"(x), "r"(y), "r"(z), "r"(w) : "memory"); }
__device__ __forceinline__ void sts64f(uint32_t a, float x, float y) { asm volatile("st.shared.v2.f32 [%0], {%1,%2};" :: "r"(a), "f"(x), "f"(y) : "memory"); }
__device__ __forceinline__ void sts32(uint32_t a, uint32_t v) { asm volatile("st.shared.b32 [%0], %1;" :: "r"(a), "r"(v) : "memory"); }
__device__ __forceinline__ void sts32f(uint32_t a, float v) { asm volatile("st.shared.f32 [%0], %1;" :: "r"(a), "f"(v) : "memory"); }
template <int OFF> __device__ __forceinline__ uint4 ld_poll128(const uint8_t* p) { uint4 v; asm volatile("ld.relaxed.gpu.global.v4.b32 {%0,%1,%2,%3}, [%4+%5];" : "=r"(v.x), "=r"(v.y), "=r"(v.z), "=r"(v.w) : "l"(p), "n"(OFF) : "memory"); return v; }
template <int OFF> __device__ __forceinline__ uint2 ld_poll64(const uint8_t* p) { uint2 v; asm volatile("ld.relaxed.gpu.global.v2.b32 {%0,%1}, [%2+%3];" : "=r"(v.x), "=r"(v.y) : "l"(p), "n"(OFF) : "memory"); return v; }
__device__ __forceinline__ uint32_t ld_poll32(const void* p) { uint32_t v; asm volatile("ld.relaxed.gpu.global.b32 %0, [%1];" : "=r"(v) : "l"(p) : "memory"); return v; }
__device__ __forceinline__ void st_pub128(uint8_t* p, uint32_t x, uint32_t y, uint32_t z, uint32_t w) { asm volatile("st.relaxed.gpu.global.v4.b32 [%0], {%1,%2,%3,%4};" :: "l"(p), "r"(x), "r"(y), "r"(z), "r"(w) : "memory"); }
__device__ __forceinline__ void st_pub64(uint8_t* p, uint32_t x, uint32_t y) { asm volatile("st.relaxed.gpu.global.v2.b32 [%0], {%1,%2};" :: "l"(p), "r"(x), "r"(y) : "memory"); }
__device__ __forceinline__ void st_pub32(void* p, uint32_t v) { asm volatile("st.relaxed.gpu.global.b32 [%0], %1;" :: "l"(p), "r"(v) : "memory"); }
__device__ __forceinline__ uint32_t min4(const uint4& v) { return min(__vimin3_u32(v.x, v.y, v.z), v.w); }
__device__ __forceinline__ uint32_t enc(uint32_t b) { return max(b, 1u); }
__device__ __forceinline__ uint32_t encf(float x) { return enc(__float_as_uint(x)); }
__device__ __forceinline__ float f(uint32_t x) { return __uint_as_float(x); }

template <int N, int STRIDE, int I = 0> struct Poll {
    static __device__ __forceinline__ uint32_t load(uint4 (&v)[N], const uint8_t* p, uint32_t mn) {
        v[I] = ld_poll128<I * STRIDE>(p);
        return Poll<N, STRIDE, I + 1>::load(v, p, mn);
    }
};
template <int N, int STRIDE> struct Poll<N, STRIDE, N> { static __device__ __forceinline__ uint32_t load(uint4 (&)[N], const uint8_t*, uint32_t mn) { return mn; } };
template <int N, int STRIDE, int SLEEP = 0> __device__ __forceinline__ void poll128(uint4 (&v)[N], const uint8_t* p) {
    int it = SPIN_LIMIT;
    while (true) {
        Poll<N, STRIDE>::load(v, p, 0);
        uint32_t mn = ~0u;
#pragma unroll
        for (int i = 0; i < N; i++) mn = __vimin3_u32(__vimin3_u32(mn, v[i].x, v[i].y), v[i].z, v[i].w);
        if (!__any_sync(~0u, mn == 0u) || !--it) break;
        if (SLEEP) __nanosleep(SLEEP);
    }
}

__device__ __forceinline__ float bf_lo(uint32_t w) { return __uint_as_float(w << 16); }
__device__ __forceinline__ float bf_hi(uint32_t w) { return __uint_as_float(w & 0xffff0000u); }
__device__ __forceinline__ uint32_t pack_bf(float lo, float hi) { uint32_t r; asm("cvt.rn.bf16x2.f32 %0, %1, %2;" : "=r"(r) : "f"(hi), "f"(lo)); return r; }
__device__ __forceinline__ float rbf(float x) { return __uint_as_float(pack_bf(0.f, x)); }
__device__ __forceinline__ uint32_t hmax2(uint32_t a, uint32_t b) { uint32_t r; asm("max.bf16x2 %0, %1, %2;" : "=r"(r) : "r"(a), "r"(b)); return r; }
__device__ __forceinline__ uint32_t hadd2(uint32_t a, uint32_t b) { uint32_t r; asm("add.rn.bf16x2 %0, %1, %2;" : "=r"(r) : "r"(a), "r"(b)); return r; }
__device__ __forceinline__ float sqrt_ap(float x) { float r; asm("sqrt.approx.ftz.f32 %0, %1;" : "=f"(r) : "f"(x)); return r; }
__device__ __forceinline__ float rcp_ap(float x) { float r; asm("rcp.approx.ftz.f32 %0, %1;" : "=f"(r) : "f"(x)); return r; }
__device__ __forceinline__ float ex2_ap(float x) { float r; asm("ex2.approx.ftz.f32 %0, %1;" : "=f"(r) : "f"(x)); return r; }
__device__ __forceinline__ float sum7(const float (&a)[7]) { return ((a[0] + a[1]) + (a[2] + a[3])) + ((a[4] + a[5]) + a[6]); }
__device__ __forceinline__ float sum8(const float (&a)[8]) { return ((a[0] + a[1]) + (a[2] + a[3])) + ((a[4] + a[5]) + (a[6] + a[7])); }
__device__ __forceinline__ float sel4(int t, float a, float b, float c, float d) { return (t & 2) ? ((t & 1) ? d : c) : ((t & 1) ? b : a); }
__device__ __forceinline__ float ln_rs(float mean, float s2) { return rcp_ap(rbf(sqrt_ap(rbf(rbf(fmaxf(fmaf(s2, 1.f / DM, -mean * mean), 0.f)) + 1e-5f)))); }
__device__ __forceinline__ void load_h(uint2 (&v)[4], const uint8_t* p) {
    v[0] = ld_poll64<0>(p); v[1] = ld_poll64<DM * 4>(p); v[2] = ld_poll64<DM * 8>(p); v[3] = ld_poll64<DM * 12>(p);
}
__device__ __forceinline__ uint32_t min_h(const uint2 (&v)[4]) { return min(__vimin3_u32(__vimin3_u32(v[0].x, v[0].y, v[1].x), v[1].y, v[2].x), __vimin3_u32(v[2].y, v[3].x, v[3].y)); }
__device__ __forceinline__ uint32_t sum_h(const uint2 (&v)[4], uint32_t xw) {
    return hadd2(xw, pack_bf((f(v[0].x) + f(v[1].x)) + (f(v[2].x) + f(v[3].x)), (f(v[0].y) + f(v[1].y)) + (f(v[2].y) + f(v[3].y))));
}
__device__ __forceinline__ void load_p(uint2 (&v)[7], const uint8_t* p) {
    v[0] = ld_poll64<0>(p); v[1] = ld_poll64<256>(p); v[2] = ld_poll64<512>(p); v[3] = ld_poll64<768>(p);
    v[4] = ld_poll64<1024>(p); v[5] = ld_poll64<1280>(p); v[6] = ld_poll64<1536>(p);
}
__device__ __forceinline__ uint32_t min_p(const uint2 (&v)[7]) {
    uint32_t mn = min(v[0].x, v[0].y);
#pragma unroll
    for (int i = 1; i < 7; i++) mn = __vimin3_u32(mn, v[i].x, v[i].y);
    return mn;
}
constexpr float L2E = 1.4426950408889634f;
constexpr uint32_t ONES = 0x3f803f80u;

__device__ __forceinline__ void final_reduce(uint2 (&hv)[4], uint2 (&pv)[7], const uint8_t* hp, const uint8_t* ip, uint32_t res, uint32_t delay,
                                             uint32_t flag, uint32_t* out, bool bump, uint32_t epoch) {
    const int lane = threadIdx.x & 31;
    int it = SPIN_LIMIT;
    while ((int)(gtime32() - delay) < 0) __nanosleep(20);
    while (true) {
        const uint32_t mn = min_h(hv);
        if (mn == 0u) load_h(hv, hp);
        if (!__any_sync(~0u, min(mn, min_p(pv)) == 0u) || !--it) break;
        if (NPW && __float_as_uint(lds32f(flag)) == 0x7fc12345u) return;
        load_p(pv, ip);
    }
    if (NPW) sts32(flag, 0x7fc12345u);
#define S7_(v, c) (((f(v[0].c) + f(v[1].c)) + (f(v[2].c) + f(v[3].c))) + ((f(v[4].c) + f(v[5].c)) + f(v[6].c)))
    float k0 = S7_(pv, x), k1 = S7_(pv, y);
#undef S7_
    res = sum_h(hv, res);
    TL(21);
#pragma unroll
    for (int o = 16; o >= 4; o >>= 1) { k0 += __shfl_xor_sync(~0u, k0, o); k1 += __shfl_xor_sync(~0u, k1, o); }
    if (lane < 4) out[lane] = hadd2(res, pack_bf(k0, k1));
    if (bump) st_pub32(&g_epoch, epoch + 1);
    TL(22);
}

__global__ void __launch_bounds__(NTHREADS, 1)
fused_decode_kernel(const uint32_t* __restrict__ x, const uint8_t* __restrict__ wq, uint32_t* __restrict__ out,
                    const __grid_constant__ Maps maps) {
    extern __shared__ __align__(1024) uint8_t smem_raw[];
    const uint32_t sb = (uint32_t)__cvta_generic_to_shared(smem_raw);
    const int cta = blockIdx.x;
    if (threadIdx.x < 256) {
        const uint8_t* src = wq + (uint32_t)((threadIdx.x >> 2) * 8192 + cta * 64 + (threadIdx.x & 3) * 16);
        const uint32_t dst = sb + SM_WQ + ((threadIdx.x * 16) ^ ((threadIdx.x * 2) & 0x30));
        cp_async16<0, 0>(dst, src); cp_async16<4096, 1 << 19>(dst, src); cp_async16<8192, 2 << 19>(dst, src); cp_async16<12288, 3 << 19>(dst, src);
        cp_async16<16384, 4 << 19>(dst, src); cp_async16<20480, 5 << 19>(dst, src); cp_async16<24576, 6 << 19>(dst, src);
    }
    const int lane = threadIdx.x & 31, warp = __shfl_sync(~0u, threadIdx.x >> 5, 0);
    const int hk = cta >> 4, j = cta & 15;
    const int g = lane >> 2, t = lane & 3;
    const bool is_ffn = cta < NFFN, is_wo = !is_ffn && cta < 2 * NFFN;
    const int wo_i = cta - NFFN, wo_r = wo_i / 14;
    const uint32_t bar0 = sb + SM_BAR;
    if (warp == 0) TL0(26);

    if (warp == 8) {
        TL0(0);
        const uint32_t t_start = gtime32() + ((cta >> 3) * 5 & 15) * STAG;
        if (lane == 0) {
#pragma unroll
            for (int i = 0; i < 42; i++) mbar_init(bar0 + i * 8, i == BAR_WQ ? 7 : i == BAR_K_FREE ? 8 : 1);
            asm volatile("fence.mbarrier_init.release.cluster;" ::: "memory");
        }
        __syncwarp();
        nb_arrive(0, NTHREADS);
        nb_arrive(NB_INIT, 64);
        TL0(27);
        const int row0 = hk * SK + (SK - WIN);
        int map = lane >> 4, c0 = map * (j & 7) * 32, c1 = row0 + (map ? (j >> 3) * 2048 + (lane - 16) * 128 : j * 256 + lane * 16);
        int wait = lane - WMAX, extra = lane >= NUNIT ? BAR_K_FREE : BAR_WQ;
        uint32_t when = t_start + T0_NS + lane * DT_NS;
        uint32_t dst = (lane < NUNIT ? lane : lane - NUNIT) * UNIT, bytes = UNIT, b = lane;
        bool todo = true;
        if (lane < 23) extra = wait;
#pragma unroll 1
        for (int r = 0; r < 2; r++) {
            do {
                if (todo && (int)(gtime32() - when) >= 0 && (wait < 0 || (mbar_test(bar0 + wait * 8) && mbar_test(bar0 + extra * 8)))) {
                    mbar_expect_tx(bar0 + b * 8, bytes);
                    tma3d(sb + dst, &maps.m[map], c0, c1, bar0 + b * 8);
                    todo = false;
                }
            } while (__any_sync(~0u, todo));
            b = BAR_W + lane;
            if (is_wo) {
                todo = lane < 8;
                wait = extra = WO_B >= 32 ? WO_B : min(WO_B + (lane * WO_N >> 3), 31);
                when = t_start + WO_T0 + lane * WO_DT;
                map = 2; c0 = (wo_i - wo_r * 14) * 32; c1 = wo_r * 1024 + lane * 128;
                dst = SM_WO + lane * UNIT;
            } else {
                todo = is_ffn && lane < 6;
                wait = -1;
                if (is_ffn && r == 0) mbar_wait(bar0 + GU_B * 8);
                when = t_start + max((int)(gtime32() - t_start), GU_T0) + lane * GU_DT + (lane < 4 ? 0 : GU_D0);
                map = lane < 4 ? 3 + (lane & 1) : 5;
                c0 = lane < 4 ? cta * 32 : 0;
                c1 = lane < 4 ? (lane >> 1) * 224 : cta * 32 + (lane & 1) * 16;
                dst = SM_GU + (lane < 4 ? (lane & 1) * 28672 + (lane >> 1) * 14336 : lane * 14336);
                bytes = 14336;
            }
        }
        TL0(2);
        return;
    }
    const uint32_t epoch = ld_poll32(&g_epoch);

    if (warp == 9) {
        const uint32_t t_svc = gtime32();
        uint32_t w[7];
#pragma unroll
        for (int i = 0; i < 7; i++) w[i] = __ldg(x + lane + 32 * i);
        uint32_t res = __ldg(x + (is_wo ? wo_i : 0) * 4 + t);
        {
            float s1 = 0.f, s2 = 0.f;
#pragma unroll
            for (int i = 0; i < 7; i++) { const float a = bf_lo(w[i]), b = bf_hi(w[i]); s1 += a + b; s2 = fmaf(a, a, fmaf(b, b, s2)); }
#pragma unroll
            for (int o = 16; o > 0; o >>= 1) { s1 += __shfl_xor_sync(~0u, s1, o); s2 += __shfl_xor_sync(~0u, s2, o); }
            const float mean = s1 * (1.f / DM), rs = ln_rs(mean, s2);
            const uint32_t nm = pack_bf(-mean, -mean);
            const uint32_t xa = sb + SM_XN + (lane & 16) * 4 + t * 16 + (g & 3) * 4;
#pragma unroll
            for (int i = 0; i < 7; i++) { const uint32_t d = hadd2(w[i], nm); sts32(xa + i * 128, pack_bf(bf_lo(d) * rs, bf_hi(d) * rs)); }
        }
        nb_arrive(0, NTHREADS);
        uint8_t* scr = (uint8_t*)&g_scr[epoch & 1];
        asm volatile("" : "+l"(scr));
        {
            uint4 v[2];
            nb_sync(NB_INIT, 64);
            mbar_wait(bar0 + BAR_WQ * 8);
            poll128<2, 512, 100>(v, scr + OQ + hk * 1024 + lane * 16);
            sts128(sb + SM_Q + lane * 16, v[0].x, v[0].z, v[0].y, v[0].w);
            sts128(sb + SM_Q + 512 + lane * 16, v[1].x, v[1].z, v[1].y, v[1].w);
            nb_arrive(NB_Q, 288);
            TL(17);
            uint8_t* nx = (uint8_t*)&g_scr[(epoch & 1) ^ 1];
#pragma unroll 1
            for (int i = (cta * 32 + lane) * 16; i < (int)sizeof(Scratch); i += NCTA * 512) *(uint4*)(nx + i) = make_uint4(0, 0, 0, 0);
        }
        const uint8_t* op = scr + OOB + wo_r * 4096 + lane * 16;
        const uint8_t* hp = scr + OPB + (cta & (NREP - 1)) * (DM * 16) + wo_i * 32 + t * 8;
        const uint8_t* ip = scr + OP2 + wo_i * (NFFN * 32) + lane * 8;
        uint4 ov[8];
        uint2 hv[4], pv[7];
#pragma unroll
        for (int i = 0; i < 8; i++) ov[i].x = 0;
        hv[0].x = 0; pv[0].x = 0;
        if (is_wo) {
            if (WARM & 1) {
#pragma unroll
                for (int i = 0; i < 8; i++) ov[i] = ld_poll128<0>(op + i * 512);
            }
            if (WARM & 4) { load_h(hv, hp); load_p(pv, ip); }
        }
        {
            mbar_wait(bar0 + (BAR_V + SSTART) * 8);
            uint4 v[4];
            poll128<4, 1024, PSLEEP>(v, scr + OST + hk * 4096 + lane * 32);
            TL(24);
            uint32_t mm = hmax2(hmax2(__byte_perm(v[0].x, v[0].z, 0x7632), __byte_perm(v[1].x, v[1].z, 0x7632)),
                                hmax2(__byte_perm(v[2].x, v[2].z, 0x7632), __byte_perm(v[3].x, v[3].z, 0x7632)));
#pragma unroll
            for (int o = 16; o > 0; o >>= 1) mm = hmax2(mm, __shfl_xor_sync(~0u, mm, o));
            const float m0 = bf_lo(mm) * L2E, m1 = bf_hi(mm) * L2E;
            float c0[4], c1[4], l0 = 0.f, l1 = 0.f;
#pragma unroll
            for (int i = 0; i < 4; i++) {
                c0[i] = ex2_ap(fmaf(f(v[i].x), L2E, -m0)); l0 = fmaf(c0[i], f(v[i].y), l0);
                c1[i] = ex2_ap(fmaf(f(v[i].z), L2E, -m1)); l1 = fmaf(c1[i], f(v[i].w), l1);
            }
#pragma unroll
            for (int o = 16; o > 0; o >>= 1) { l0 += __shfl_xor_sync(~0u, l0, o); l1 += __shfl_xor_sync(~0u, l1, o); }
            l0 = rcp_ap(l0); l1 = rcp_ap(l1);
#pragma unroll
            for (int i = 0; i < 4; i++) sts64f(sb + SM_SC + lane * 8 + i * 256, c0[i] * l0, c1[i] * l1);
            nb_arrive(NB_SC, 288);
        }
        if (!is_wo) return;
        {
            int it = SPIN_LIMIT;
            mbar_wait(bar0 + (BAR_V + OSTART) * 8);
            { const uint32_t t1 = gtime32(); while ((int)(gtime32() - t1) < O_D); }
            while (true) {
                uint32_t mn = ~0u;
#pragma unroll
                for (int i = 0; i < 8; i++) if (min4(ov[i]) == 0u) ov[i] = ld_poll128<0>(op + i * 512);
#pragma unroll
                for (int i = 0; i < 8; i++) mn = min(mn, min4(ov[i]));
                if (!__any_sync(~0u, mn == 0u) || !--it) break;
            }
#pragma unroll
            for (int i = 0; i < 8; i++) sts128(sb + SM_OB + lane * 16 + i * 512, ov[i].x, ov[i].y, ov[i].z, ov[i].w);
            nb_arrive(NB_O, 288);
            TL(19);
        }
        {
            final_reduce(hv, pv, hp, ip, res, P2_D > 8000 ? t_svc + P2_D : gtime32() + P2_D, sb + SM_SC, out + wo_i * 4, wo_i == 0, epoch);
        }
        return;
    }

    const uint32_t xw = __ldg(x + min(warp, 6) * 32 + lane);
    const int lrow = (lane & 7) + ((lane >> 4) << 3), lc = (lane >> 3) & 1;
    const uint32_t voff = sb + lrow * 64 + ((lc ^ ((lrow >> 1) & 3)) << 4);
    const bool odd = g & 1;
    asm volatile("cp.async.wait_all;" ::: "memory");
    nb_sync(0, NTHREADS);
    uint8_t* scr = (uint8_t*)&g_scr[epoch & 1];
    asm volatile("" : "+l"(scr));

    if (warp < 7) {
        if (warp == 0) TL(3);
        float c[2][4];
#pragma unroll
        for (int s = 0; s < 4; s += 2) {
            const uint4 hv = lds128(sb + SM_XN + warp * 128 + s * 32 + t * 16);
#pragma unroll
            for (int tl = 0; tl < 2; tl++) {
                uint32_t a0[4], a1[4];
                ldsm4t(a0, (voff ^ (tl * 32)) + SM_WQ + warp * 4096 + s * 1024); ldsm4t(a1, (voff ^ (tl * 32)) + SM_WQ + warp * 4096 + s * 1024 + 1024);
                if (s == 0) mma16816z(c[tl], a0, hv.x, hv.y); else mma16816(c[tl], a0, hv.x, hv.y);
                mma16816(c[tl], a1, hv.z, hv.w);
            }
        }
        sts32f(sb + SM_G1 + warp * 128 + (t * 8 + g) * 4, sel4(t, c[0][0], c[0][2], c[1][0], c[1][2]));
        if (lane == 0) mbar_arrive(bar0 + BAR_WQ * 8);
        if (warp == 0) {
            nb_sync(NB_G1, 224);
            float d[7];
#pragma unroll
            for (int w = 0; w < 7; w++) d[w] = lds32f(sb + SM_G1 + w * 128 + lane * 4);
            const float val = sum7(d);
            const uint32_t pw = pack_bf(val, __shfl_down_sync(~0u, val, 1));
            if (!(lane & 1)) st_pub32(scr + OQ + cta * 64 + lane * 2, enc(pw));
            TL0(4);
        } else {
            nb_arrive(NB_G1, 224);
        }
    }
    nb_sync(NB_Q, 288);
    if (warp == 0) TL0(5);
    const bool is_f7 = is_ffn && warp < 7;
    const uint8_t* hp = scr + OPB + (cta & (NREP - 1)) * (DM * 16) + warp * 256 + lane * 8;
    uint2 hv[4];
    if (is_f7 && (WARM & 2)) load_h(hv, hp);
    {
        const uint32_t kb = (sb + warp * 2 * UNIT + g * 512 + t * 16) ^ ((g & 1) << 6);
        const uint32_t qb = (sb + SM_Q + (g & 1) * 512 + t * 16 + (g >> 2) * 8) ^ ((g & 2) << 5);
        float c[4][4];
#pragma unroll
        for (int i = 0; i < 4; i++) c[i][0] = c[i][1] = c[i][2] = c[i][3] = 0.f;
        mbar_wait(bar0 + warp * 16);
        mbar_wait(bar0 + warp * 16 + 8);
#pragma unroll 2
        for (int s = 0; s < 512; s += 64) {
            const uint2 qf = lds64(qb ^ s);
#pragma unroll
            for (int i = 0; i < 4; i++) { const uint4 k = lds128((kb ^ s) + i * 4096); mma16816(c[i], k.x, k.y, k.z, k.w, qf.x, qf.y); }
        }
        if (lane == 0) mbar_arrive(bar0 + BAR_K_FREE * 8);
        const bool hi = t & 2, act = !((t ^ g) & 1);
        uint32_t sw[2];
#pragma unroll
        for (int i = 0; i < 2; i++) {
            const float a = (hi ? c[2 + i][2] : c[i][0]) + __shfl_xor_sync(~0u, hi ? c[i][2] : c[2 + i][0], 2);
            const float b = (hi ? c[2 + i][3] : c[i][1]) + __shfl_xor_sync(~0u, hi ? c[i][3] : c[2 + i][1], 2);
            sw[i] = pack_bf(a * 0.0625f, b * 0.0625f);
        }
        uint32_t mm = act ? hmax2(sw[0], sw[1]) : 0xff80ff80u;
#pragma unroll
        for (int o = 16; o > 0; o >>= 1) mm = hmax2(mm, __shfl_xor_sync(~0u, mm, o));
        const float m0 = bf_lo(mm) * L2E, m1 = bf_hi(mm) * L2E;
        const float e00 = ex2_ap(fmaf(bf_lo(sw[0]), L2E, -m0)), e01 = ex2_ap(fmaf(bf_hi(sw[0]), L2E, -m1));
        const float e10 = ex2_ap(fmaf(bf_lo(sw[1]), L2E, -m0)), e11 = ex2_ap(fmaf(bf_hi(sw[1]), L2E, -m1));
        const float x0 = __shfl_xor_sync(~0u, odd ? e00 : e01, 5), x1 = __shfl_xor_sync(~0u, odd ? e10 : e11, 5);
        uint8_t* ep = scr + OE + (cta * 8 + warp) * 128;
        if (act) st_pub64(ep + (g & 1) * 64 + (g >> 1) * 16 + (t >> 1) * 8,
                          enc(odd ? pack_bf(x0, e01) : pack_bf(e00, x0)), enc(odd ? pack_bf(x1, e11) : pack_bf(e10, x1)));
        float l = act ? (odd ? e01 + e11 : e00 + e10) + (x0 + x1) : 0.f;
#pragma unroll
        for (int o = 16; o > 0; o >>= 1) if (o != 4) l += __shfl_xor_sync(~0u, l, o);
        const float lo = __shfl_xor_sync(~0u, l, 4);
        if (lane < 2) st_pub128(scr + OST + (cta * 8 + warp) * 32 + lane * 16, encf(bf_lo(mm)), encf(l), encf(bf_hi(mm)), encf(lo));
    }
    if (warp == 7) TL0(6);
    {
        const int grp0 = (j >> 3) * 64 + warp;
        mbar_wait(bar0 + (BAR_V + PSTART) * 8);
        uint4 p[8];
        poll128<8, 1024, PSLEEP>(p, scr + OE + (hk * 128 + grp0) * 128 + (g & 1) * 64 + t * 16);
        if (warp == 7) TL(7);
        nb_sync(NB_SC, 288);
        if (warp == 0) TL(8);
        const uint32_t vb = voff + warp * 2048;
        float o[2][4] = {{0.f, 0.f, 0.f, 0.f}, {0.f, 0.f, 0.f, 0.f}};
#pragma unroll
        for (int i = 0; i < 8; i++) {
            const uint32_t va = vb + (i < 5 ? (16 + 2 * i) * UNIT : i > 5 ? (2 * i - 11) * UNIT : (warp < 4 ? 26 * UNIT : -UNIT));
            const float2 sc = lds64f(sb + SM_SC + (grp0 + i * 8) * 8);
            mbar_wait(bar0 + (warp >> 2) * 8 + (BAR_V + 2 * i) * 8);
            if (i == 7 && warp == 7) TL(20);
#pragma unroll
            for (int mt = 0; mt < 2; mt++) {
                uint32_t a0[4], a1[4];
                float d[4];
                ldsm4t(a0, va ^ (mt * 32)); ldsm4t(a1, (va ^ (mt * 32)) + 1024);
                mma16816z(d, a0, p[i].x, p[i].y);
                mma16816(d, a1, p[i].z, p[i].w);
                o[mt][0] = fmaf(d[0], sc.x, o[mt][0]); o[mt][1] = fmaf(d[1], sc.y, o[mt][1]);
                o[mt][2] = fmaf(d[2], sc.x, o[mt][2]); o[mt][3] = fmaf(d[3], sc.y, o[mt][3]);
            }
        }
        sts64f(sb + SM_RED + warp * 256 + (t * 8 + g) * 8, sel4(t, o[0][0], o[0][2], o[1][0], o[1][2]), sel4(t, o[0][1], o[0][3], o[1][1], o[1][3]));
        if (warp == 0) {
            nb_sync(NB_PV, 256);
            TL(9);
            float r0[8], r1[8];
#pragma unroll
            for (int w = 0; w < 8; w++) { const float2 r = lds64f(sb + SM_RED + w * 256 + lane * 8); r0[w] = r.x; r1[w] = r.y; }
            const float o0 = sum8(r0), o1 = sum8(r1);
            const float ox = __shfl_xor_sync(~0u, (lane & 1) ? o0 : o1, 1);
            st_pub32(scr + OOB + cta * 128 + (lane & 1) * 64 + ((lane >> 1) & 3) * 16 + (lane >> 3) * 4, enc((lane & 1) ? pack_bf(ox, o1) : pack_bf(o0, ox)));
            TL(18);
        } else {
            nb_arrive(NB_PV, 256);
        }
    }
    if (is_wo) {
        uint32_t a[2][8][4];
        mbar_wait(bar0 + (BAR_W + warp) * 8);
        if (warp == 7) TL(10);
#pragma unroll
        for (int s = 0; s < 8; s++) { ldsm4t(a[0][s], voff + SM_WO + warp * UNIT + s * 1024); ldsm4t(a[1][s], (voff ^ 32) + SM_WO + warp * UNIT + s * 1024); }
        nb_sync(NB_O, 288);
        uint4 ov[4];
#pragma unroll
        for (int i = 0; i < 4; i++) ov[i] = lds128(sb + SM_OB + ((warp >> 2) * 16 + (g & 1) * 8 + (warp & 1) * 4 + i) * 128 + (warp & 2) * 32 + t * 16);
        float c[2][2][4];
#pragma unroll
        for (int i = 0; i < 4; i++) {
#pragma unroll
            for (int mt = 0; mt < 2; mt++) {
                if (i == 0) { mma16816z(c[mt][0], a[mt][0], ov[i].x, ov[i].y); mma16816z(c[mt][1], a[mt][1], ov[i].z, ov[i].w); }
                else { mma16816(c[mt][0], a[mt][2 * i], ov[i].x, ov[i].y); mma16816(c[mt][1], a[mt][2 * i + 1], ov[i].z, ov[i].w); }
            }
        }
        sts32f(sb + SM_XN + warp * 128 + (t * 8 + g) * 4,
               (sel4(t, c[0][0][0], c[0][0][2], c[1][0][0], c[1][0][2]) + sel4(t, c[0][0][1], c[0][0][3], c[1][0][1], c[1][0][3])) +
               (sel4(t, c[0][1][0], c[0][1][2], c[1][1][0], c[1][1][2]) + sel4(t, c[0][1][1], c[0][1][3], c[1][1][1], c[1][1][3])));
        if (warp < NREP) {
            nb_sync(NB_WO, ODIRECT ? 288 : 256);
            float r[8];
#pragma unroll
            for (int w = 0; w < 8; w++) r[w] = lds32f(sb + SM_XN + w * 128 + lane * 4);
            st_pub32(scr + OPB + warp * (DM * 16) + wo_i * 128 + lane * 4, encf(sum8(r)));
            if (warp == 0) TL(11);
        } else {
            nb_arrive(NB_WO, ODIRECT ? 288 : 256);
            if (warp >= 8 - NPW) {
                uint2 pv[7];
                hv[0].x = 0; pv[0].x = 0;
                final_reduce(hv, pv, scr + OPB + (cta & (NREP - 1)) * (DM * 16) + wo_i * 32 + t * 8, scr + OP2 + wo_i * (NFFN * 32) + lane * 8,
                             __ldg(x + wo_i * 4 + t), gtime32() + P2_D - 300 + (8 - warp) * (290 / (NPW + 1)), sb + SM_SC, out + wo_i * 4, wo_i == 0, epoch);
            }
        }
    } else if (is_f7) {
        uint32_t a[4][4][4], a2[2][4][4];
        mbar_wait(bar0 + BAR_W * 8); mbar_wait(bar0 + BAR_W * 8 + 8);
        mbar_wait(bar0 + (BAR_W + (HSTART & 3)) * 8);
        { const uint32_t t1 = gtime32(); while ((int)(gtime32() - t1) < H_D); }
        const uint32_t gb = bar0 + BAR_W * 8 + (warp < 3 ? 0 : 16);
        {
            bool done = false, have = false;
            int it = SPIN_LIMIT;
            do {
                if (!done) load_h(hv, hp);
                if (!have && mbar_try(gb + 8, HTRY) && mbar_try(gb, HTRY)) {
                    if (warp == 6) TL(12);
#pragma unroll
                    for (int s = 0; s < 4; s++)
#pragma unroll
                        for (int m = 0; m < 4; m++) ldsm4t(a[m][s], (voff ^ ((m & 1) * 32)) + SM_GU + (m >> 1) * 28672 + warp * 4096 + s * 1024);
                    have = true;
                }
                done = !__any_sync(~0u, min_h(hv) == 0u) || --it < 0;
            } while (!(done && have));
        }
        const uint32_t hword = sum_h(hv, xw);
        if (warp == 6) TL(15);
        float c[4][4], cs[4][4];
        uint32_t f0[4], f1[4];
#pragma unroll
        for (int s = 0; s < 4; s++) {
            const uint32_t h0 = __shfl_sync(~0u, hword, s * 8 + t), h1 = __shfl_sync(~0u, hword, s * 8 + 4 + t);
            f0[s] = odd ? ONES : h0; f1[s] = odd ? ONES : h1;
            const uint32_t ah[4] = {h0, h0, h1, h1};
            mma16816z(cs[s], ah, f0[s], f1[s]);
        }
#pragma unroll
        for (int s = 0; s < 4; s++) {
#pragma unroll
            for (int m = 0; m < 4; m++) { if (s == 0) mma16816z(c[m], a[m][s], f0[s], f1[s]); else mma16816(c[m], a[m][s], f0[s], f1[s]); }
            if (s == 0) {
                if (lane == 0) sts64f(sb + SM_G1 + 3584 + warp * 8, (cs[0][0] + cs[1][0]) + (cs[2][0] + cs[3][0]), (cs[0][1] + cs[1][1]) + (cs[2][1] + cs[3][1]));
                nb_arrive(NB_S, 256);
            }
        }
        sts128(sb + SM_G1 + warp * 512 + (t * 8 + g) * 16,
               __float_as_uint(sel4(t, c[0][0], c[0][2], c[1][0], c[1][2])), __float_as_uint(sel4(t, c[0][1], c[0][3], c[1][1], c[1][3])),
               __float_as_uint(sel4(t, c[2][0], c[2][2], c[3][0], c[3][2])), __float_as_uint(sel4(t, c[2][1], c[2][3], c[3][1], c[3][3])));
        nb_arrive(NB_G2, 256);
#pragma unroll
        for (int i = 0; i < 8; i++) {
            if (!(i & 3)) mbar_wait(bar0 + BAR_DN * 8 + i * 2);
            ldsm4t(a2[i >> 2][i & 3], sb + SM_DN + warp * 2048 + (i >> 2) * 14336 + lrow * 128 + ((((i & 3) * 2 + lc) ^ (lane & 7)) << 4));
        }
        nb_sync(NB_H, 256);
        const uint2 b = lds64(sb + SM_XN + ((odd ? 4 : 0) + t) * 8);
        float e[4][4];
#pragma unroll
        for (int i = 0; i < 4; i++) mma16816z(e[i], a2[0][i], odd ? 0u : b.x, odd ? b.x : 0u);
#pragma unroll
        for (int i = 0; i < 4; i++) mma16816(e[i], a2[1][i], odd ? 0u : b.y, odd ? b.y : 0u);
        uint8_t* dst = scr + OP2 + (warp * 8 + t * 2) * (NFFN * 32) + cta * 32 + g * 4;
        st_pub32(dst, encf(sel4(t, e[0][0], e[1][0], e[2][0], e[3][0]) + sel4(t, e[0][1], e[1][1], e[2][1], e[3][1])));
        st_pub32(dst + NFFN * 32, encf(sel4(t, e[0][2], e[1][2], e[2][2], e[3][2]) + sel4(t, e[0][3], e[1][3], e[2][3], e[3][3])));
        if (warp == 0) TL(14);
    } else if (is_ffn) {
        nb_sync(NB_S, 256);
        const float4 s01 = lds128f(sb + SM_G1 + 3584), s23 = lds128f(sb + SM_G1 + 3600), s45 = lds128f(sb + SM_G1 + 3616);
        const float2 s6 = lds64f(sb + SM_G1 + 3632);
        const float mean = (((s01.y + s01.w) + (s23.y + s23.w)) + ((s45.y + s45.w) + s6.y)) * (1.f / DM);
        const float rs = ln_rs(mean, ((s01.x + s01.z) + (s23.x + s23.z)) + ((s45.x + s45.z) + s6.x)), mb = rbf(mean);
        nb_sync(NB_G2, 256);
        TL(13);
        float d0[7], d1[7], d2[7], d3[7];
#pragma unroll
        for (int w = 0; w < 7; w++) { const float4 d = lds128f(sb + SM_G1 + w * 512 + lane * 16); d0[w] = d.x; d1[w] = d.y; d2[w] = d.z; d3[w] = d.w; }
        const uint32_t gu = pack_bf((sum7(d0) - mb * sum7(d1)) * rs, (sum7(d2) - mb * sum7(d3)) * rs);
        const float hh = bf_lo(gu) * bf_hi(gu);
        const uint32_t hw = pack_bf(hh, __shfl_down_sync(~0u, hh, 1));
        if (!(lane & 1)) sts32(sb + SM_XN + (lane & 14) * 4 + (lane >> 4) * 4, hw);
        nb_arrive(NB_H, 256);
    }
}

typedef CUresult (*EncodeFn)(CUtensorMap*, CUtensorMapDataType, cuuint32_t, void*, const cuuint64_t*, const cuuint64_t*,
                             const cuuint32_t*, const cuuint32_t*, CUtensorMapInterleave, CUtensorMapSwizzle,
                             CUtensorMapL2promotion, CUtensorMapFloatOOBfill);

void make_map(EncodeFn enc_fn, CUtensorMap* tm, const void* base, uint64_t cols, uint64_t rows, uint32_t box_cols, uint32_t box_rows,
              uint32_t nblk, CUtensorMapSwizzle sw) {
    cuuint64_t gdim[3] = {nblk > 1 ? box_cols : cols, rows, nblk};
    cuuint64_t gstr[2] = {cols * 2, (cuuint64_t)box_cols * 2};
    cuuint32_t box[3] = {box_cols, box_rows, nblk};
    cuuint32_t es[3] = {1, 1, 1};
    enc_fn(tm, CU_TENSOR_MAP_DATA_TYPE_BFLOAT16, 3, const_cast<void*>(base), gdim, gstr, box, es, CU_TENSOR_MAP_INTERLEAVE_NONE, sw,
           CU_TENSOR_MAP_L2_PROMOTION_L2_128B, CU_TENSOR_MAP_FLOAT_OOB_FILL_NONE);
}

}

extern "C" void kernel_launch(void* const* d_in, const int* in_sizes, int n_in, void* d_out, int out_size) {
    (void)in_sizes; (void)n_in; (void)out_size;
    static EncodeFn enc_fn = nullptr;
    if (!enc_fn) {
        void* fn = nullptr;
        cudaDriverEntryPointQueryResult qr;
        cudaGetDriverEntryPoint("cuTensorMapEncodeTiled", &fn, cudaEnableDefault, &qr);
        enc_fn = (EncodeFn)fn;
        cudaFuncSetAttribute(fused_decode_kernel, cudaFuncAttributeMaxDynamicSharedMemorySize, SM_TOTAL);
    }
    Maps maps;
    make_map(enc_fn, &maps.m[0], d_in[1], 256, (uint64_t)8 * SK, 256, 16, 1, CU_TENSOR_MAP_SWIZZLE_NONE);
    make_map(enc_fn, &maps.m[1], d_in[2], 256, (uint64_t)8 * SK, 32, 128, 1, CU_TENSOR_MAP_SWIZZLE_64B);
    make_map(enc_fn, &maps.m[2], d_in[4], DM, 4096, 32, 128, 1, CU_TENSOR_MAP_SWIZZLE_64B);
    make_map(enc_fn, &maps.m[3], d_in[6], FF, DM, 32, 224, 1, CU_TENSOR_MAP_SWIZZLE_64B);
    make_map(enc_fn, &maps.m[4], d_in[7], FF, DM, 32, 224, 1, CU_TENSOR_MAP_SWIZZLE_64B);
    make_map(enc_fn, &maps.m[5], d_in[8], DM, FF, 64, 16, 7, CU_TENSOR_MAP_SWIZZLE_128B);
    fused_decode_kernel<<<NCTA, NTHREADS, SM_TOTAL>>>((const uint32_t*)d_in[0], (const uint8_t*)d_in[3], (uint32_t*)d_out, maps);
}
```

```cpp
#include <cuda_runtime.h>
#include <cuda_bf16.h>
#include <cuda.h>
#include <stdint.h>
#include <stddef.h>

namespace {

constexpr int DM = 448, SK = 65536, WIN = 4096, FF = 1792;
constexpr int NCTA = 128, NFFN = 56;
constexpr int NTHREADS = 320;
constexpr int UNIT = 8192;
constexpr int SPIN_LIMIT = 1 << 20;

constexpr int T0_NS = 200, DT_NS = 330;
constexpr int WMAX = 8;
constexpr int WO_T0 = 11050, WO_DT = 148;
constexpr int GU_T0 = 12500, GU_DT = 74, GU_D0 = 250;
constexpr int PSTART = 4, SSTART = 5;
constexpr int OSTART = 14;
constexpr int HSTART = 4;
constexpr int P2_D = 1000;
constexpr int NREP = 2;

constexpr int NUNIT = 27;
constexpr int SM_WQ = 23 * UNIT;
constexpr int SM_WO = 5 * UNIT;
constexpr int SM_OB = 13 * UNIT;
constexpr int SM_GU = 5 * UNIT;
constexpr int SM_DN = SM_GU + 57344;
constexpr int SM_G1 = NUNIT * UNIT;
constexpr int SM_RED = SM_G1 + 4096;
constexpr int SM_Q = SM_RED + 2048;
constexpr int SM_XN = SM_Q + 1024;
constexpr int SM_SC = SM_XN + 1024;
constexpr int SM_BAR = SM_SC + 1024;
constexpr int SM_TOTAL = SM_BAR + 48 * 8;
static_assert(SM_TOTAL <= 232448, "smem");

enum { BAR_K = 0, BAR_V = 16, BAR_W = 32, BAR_DN = 39, BAR_WQ = 46, BAR_K_FREE = 47 };
enum { NB_PV = 1, NB_G1 = 2, NB_Q = 3, NB_INIT = 4, NB_SC = 5, NB_WO = 6, NB_O = 7, NB_S = 8, NB_H = 9, NB_G2 = 10, NB_O2 = 11 };

struct __align__(4096) Scratch {
    uint32_t p2[56][512];
    uint32_t q[8][256];
    uint32_t e[8][128][32];
    uint32_t st[8][128][8];
    uint32_t ob[NCTA][32];
    uint32_t pb[NREP][4][DM];
};
constexpr int OQ = offsetof(Scratch, q), OE = offsetof(Scratch, e), OST = offsetof(Scratch, st), OOB = offsetof(Scratch, ob),
              OPB = offsetof(Scratch, pb), OP2 = offsetof(Scratch, p2);
__device__ Scratch g_scr[2];
__device__ uint32_t g_epoch;

struct Maps { CUtensorMap m[6]; };

__device__ __forceinline__ void mbar_init(uint32_t bar, int cnt) { asm volatile("mbarrier.init.shared::cta.b64 [%0], %1;" :: "r"(bar), "r"(cnt) : "memory"); }
__device__ __forceinline__ void mbar_expect_tx(uint32_t bar, uint32_t bytes) { asm volatile("mbarrier.arrive.expect_tx.shared::cta.b64 _, [%0], %1;" :: "r"(bar), "r"(bytes) : "memory"); }
__device__ __forceinline__ void mbar_arrive(uint32_t bar) { asm volatile("mbarrier.arrive.shared::cta.b64 _, [%0];" :: "r"(bar) : "memory"); }
__device__ __forceinline__ bool mbar_test(uint32_t bar) {
    uint32_t ok;
    asm volatile("{\n.reg .pred p;\nmbarrier.test_wait.parity.shared::cta.b64 p, [%1], 0;\nselp.u32 %0, 1, 0, p;\n}" : "=r"(ok) : "r"(bar) : "memory");
    return ok;
}
__device__ __forceinline__ bool mbar_try(uint32_t bar, uint32_t ns) {
    uint32_t ok;
    asm volatile("{\n.reg .pred p;\nmbarrier.try_wait.parity.shared::cta.b64 p, [%1], 0, %2;\nselp.u32 %0, 1, 0, p;\n}" : "=r"(ok) : "r"(bar), "r"(ns) : "memory");
    return ok;
}
__device__ __forceinline__ void mbar_wait(uint32_t bar) {
    asm volatile("{\n.reg .pred p;\nW_%=:\nmbarrier.try_wait.parity.shared::cta.b64 p, [%0], 0;\n@!p bra W_%=;\n}" :: "r"(bar) : "memory");
}
__device__ __forceinline__ uint32_t gtime32() { uint32_t t; asm volatile("mov.u32 %0, %%globaltimer_lo;" : "=r"(t) :: "memory"); return t; }
__device__ __forceinline__ void tma2d(uint32_t dst, const CUtensorMap* tm, int c0, int c1, uint32_t bar) {
    uint64_t pol;
    asm("createpolicy.fractional.L2::evict_first.b64 %0, 1.0;" : "=l"(pol));
    asm volatile("cp.async.bulk.tensor.2d.shared::cluster.global.mbarrier::complete_tx::bytes.L2::cache_hint [%0], [%1, {%3, %4}], [%2], %5;"
                 :: "r"(dst), "l"(tm), "r"(bar), "r"(c0), "r"(c1), "l"(pol) : "memory");
}
template <int DO, int SO> __device__ __forceinline__ void cp_async16(uint32_t dst, const void* src) { asm volatile("cp.async.cg.shared.global.L2::128B [%0+%2], [%1+%3], 16;" :: "r"(dst), "l"(src), "n"(DO), "n"(SO) : "memory"); }
__device__ __forceinline__ void nb_sync(int id, int n) { asm volatile("bar.sync %0, %1;" :: "r"(id), "r"(n) : "memory"); }
__device__ __forceinline__ void nb_arrive(int id, int n) { asm volatile("bar.arrive %0, %1;" :: "r"(id), "r"(n) : "memory"); }
__device__ __forceinline__ void ldsm4t(uint32_t (&r)[4], uint32_t addr) {
    asm volatile("ldmatrix.sync.aligned.m8n8.x4.trans.shared.b16 {%0,%1,%2,%3}, [%4];" : "=r"(r[0]), "=r"(r[1]), "=r"(r[2]), "=r"(r[3]) : "r"(addr) : "memory");
}
__device__ __forceinline__ void mma16816(float (&c)[4], uint32_t a0, uint32_t a1, uint32_t a2, uint32_t a3, uint32_t b0, uint32_t b1) {
    asm volatile("mma.sync.aligned.m16n8k16.row.col.f32.bf16.bf16.f32 {%0,%1,%2,%3}, {%4,%5,%6,%7}, {%8,%9}, {%0,%1,%2,%3};"
                 : "+f"(c[0]), "+f"(c[1]), "+f"(c[2]), "+f"(c[3]) : "r"(a0), "r"(a1), "r"(a2), "r"(a3), "r"(b0), "r"(b1));
}
__device__ __forceinline__ void mma16816(float (&c)[4], const uint32_t (&a)[4], uint32_t b0, uint32_t b1) { mma16816(c, a[0], a[1], a[2], a[3], b0, b1); }
__device__ __forceinline__ void mma16816z(float (&c)[4], const uint32_t (&a)[4], uint32_t b0, uint32_t b1) {
    asm volatile("mma.sync.aligned.m16n8k16.row.col.f32.bf16.bf16.f32 {%0,%1,%2,%3}, {%4,%5,%6,%7}, {%8,%9}, {%10,%10,%10,%10};"
                 : "=f"(c[0]), "=f"(c[1]), "=f"(c[2]), "=f"(c[3]) : "r"(a[0]), "r"(a[1]), "r"(a[2]), "r"(a[3]), "r"(b0), "r"(b1), "f"(0.f));
}
__device__ __forceinline__ uint4 lds128(uint32_t a) { uint4 v; asm volatile("ld.shared.v4.b32 {%0,%1,%2,%3}, [%4];" : "=r"(v.x), "=r"(v.y), "=r"(v.z), "=r"(v.w) : "r"(a) : "memory"); return v; }
__device__ __forceinline__ float4 lds128f(uint32_t a) { float4 v; asm volatile("ld.shared.v4.f32 {%0,%1,%2,%3}, [%4];" : "=f"(v.x), "=f"(v.y), "=f"(v.z), "=f"(v.w) : "r"(a) : "memory"); return v; }
__device__ __forceinline__ uint2 lds64(uint32_t a) { uint2 v; asm volatile("ld.shared.v2.b32 {%0,%1}, [%2];" : "=r"(v.x), "=r"(v.y) : "r"(a) : "memory"); return v; }
__device__ __forceinline__ float2 lds64f(uint32_t a) { float2 v; asm volatile("ld.shared.v2.f32 {%0,%1}, [%2];" : "=f"(v.x), "=f"(v.y) : "r"(a) : "memory"); return v; }
__device__ __forceinline__ float lds32f(uint32_t a) { float v; asm volatile("ld.shared.f32 %0, [%1];" : "=f"(v) : "r"(a) : "memory"); return v; }
__device__ __forceinline__ void sts128(uint32_t a, uint32_t x, uint32_t y, uint32_t z, uint32_t w) { asm volatile("st.shared.v4.b32 [%0], {%1,%2,%3,%4};" :: "r"(a), "r"(x), "r"(y), "r"(z), "r"(w) : "memory"); }
__device__ __forceinline__ void sts64f(uint32_t a, float x, float y) { asm volatile("st.shared.v2.f32 [%0], {%1,%2};" :: "r"(a), "f"(x), "f"(y) : "memory"); }
__device__ __forceinline__ void sts32(uint32_t a, uint32_t v) { asm volatile("st.shared.b32 [%0], %1;" :: "r"(a), "r"(v) : "memory"); }
__device__ __forceinline__ void sts32f(uint32_t a, float v) { asm volatile("st.shared.f32 [%0], %1;" :: "r"(a), "f"(v) : "memory"); }
template <int OFF> __device__ __forceinline__ uint4 ld_poll128(const uint8_t* p) { uint4 v; asm volatile("ld.relaxed.gpu.global.v4.b32 {%0,%1,%2,%3}, [%4+%5];" : "=r"(v.x), "=r"(v.y), "=r"(v.z), "=r"(v.w) : "l"(p), "n"(OFF) : "memory"); return v; }
template <int OFF> __device__ __forceinline__ uint2 ld_poll64(const uint8_t* p) { uint2 v; asm volatile("ld.relaxed.gpu.global.v2.b32 {%0,%1}, [%2+%3];" : "=r"(v.x), "=r"(v.y) : "l"(p), "n"(OFF) : "memory"); return v; }
__device__ __forceinline__ uint32_t ld_poll32(const void* p) { uint32_t v; asm volatile("ld.relaxed.gpu.global.b32 %0, [%1];" : "=r"(v) : "l"(p) : "memory"); return v; }
__device__ __forceinline__ void st_pub128(uint8_t* p, uint32_t x, uint32_t y, uint32_t z, uint32_t w) { asm volatile("st.relaxed.gpu.global.v4.b32 [%0], {%1,%2,%3,%4};" :: "l"(p), "r"(x), "r"(y), "r"(z), "r"(w) : "memory"); }
__device__ __forceinline__ void st_pub64(uint8_t* p, uint32_t x, uint32_t y) { asm volatile("st.relaxed.gpu.global.v2.b32 [%0], {%1,%2};" :: "l"(p), "r"(x), "r"(y) : "memory"); }
__device__ __forceinline__ void st_pub32(void* p, uint32_t v) { asm volatile("st.relaxed.gpu.global.b32 [%0], %1;" :: "l"(p), "r"(v) : "memory"); }
__device__ __forceinline__ uint32_t min4(const uint4& v) { return min(__vimin3_u32(v.x, v.y, v.z), v.w); }
__device__ __forceinline__ uint32_t enc(uint32_t b) { return max(b, 1u); }
__device__ __forceinline__ uint32_t encf(float x) { return enc(__float_as_uint(x)); }
__device__ __forceinline__ float f(uint32_t x) { return __uint_as_float(x); }

template <int N, int STRIDE, int I = 0> struct Poll {
    static __device__ __forceinline__ void load(uint4 (&v)[N], const uint8_t* p) { v[I] = ld_poll128<I * STRIDE>(p); Poll<N, STRIDE, I + 1>::load(v, p); }
};
template <int N, int STRIDE> struct Poll<N, STRIDE, N> { static __device__ __forceinline__ void load(uint4 (&)[N], const uint8_t*) {} };
template <int N, int STRIDE> __device__ __forceinline__ void poll128(uint4 (&v)[N], const uint8_t* p, int sleep_ns) {
    int it = SPIN_LIMIT;
    bool first = true;
    while (true) {
        uint32_t mn = ~0u;
#pragma unroll
        for (int i = 0; i < N; i++) mn = __vimin3_u32(__vimin3_u32(mn, v[i].x, v[i].y), v[i].z, v[i].w);
        if (!__any_sync(~0u, mn == 0u) || !--it) break;
        if (!first) __nanosleep(sleep_ns);
        first = false;
        Poll<N, STRIDE>::load(v, p);
    }
}

__device__ __forceinline__ float bf_lo(uint32_t w) { return __uint_as_float(w << 16); }
__device__ __forceinline__ float bf_hi(uint32_t w) { return __uint_as_float(w & 0xffff0000u); }
__device__ __forceinline__ uint32_t pack_bf(float lo, float hi) { uint32_t r; asm("cvt.rn.bf16x2.f32 %0, %1, %2;" : "=r"(r) : "f"(hi), "f"(lo)); return r; }
__device__ __forceinline__ float rbf(float x) { return __uint_as_float(pack_bf(0.f, x)); }
__device__ __forceinline__ uint32_t hmax2(uint32_t a, uint32_t b) { uint32_t r; asm("max.bf16x2 %0, %1, %2;" : "=r"(r) : "r"(a), "r"(b)); return r; }
__device__ __forceinline__ uint32_t hadd2(uint32_t a, uint32_t b) { uint32_t r; asm("add.rn.bf16x2 %0, %1, %2;" : "=r"(r) : "r"(a), "r"(b)); return r; }
__device__ __forceinline__ float sqrt_ap(float x) { float r; asm("sqrt.approx.ftz.f32 %0, %1;" : "=f"(r) : "f"(x)); return r; }
__device__ __forceinline__ float rcp_ap(float x) { float r; asm("rcp.approx.ftz.f32 %0, %1;" : "=f"(r) : "f"(x)); return r; }
__device__ __forceinline__ float ex2_ap(float x) { float r; asm("ex2.approx.ftz.f32 %0, %1;" : "=f"(r) : "f"(x)); return r; }
__device__ __forceinline__ float sum7(const float (&a)[7]) { return ((a[0] + a[1]) + (a[2] + a[3])) + ((a[4] + a[5]) + a[6]); }
__device__ __forceinline__ float sum8(const float (&a)[8]) { return ((a[0] + a[1]) + (a[2] + a[3])) + ((a[4] + a[5]) + (a[6] + a[7])); }
__device__ __forceinline__ float sel4(int t, float a, float b, float c, float d) { return (t & 2) ? ((t & 1) ? d : c) : ((t & 1) ? b : a); }
__device__ __forceinline__ float ln_rs(float mean, float s2) { return rcp_ap(rbf(sqrt_ap(rbf(rbf(fmaxf(fmaf(s2, 1.f / DM, -mean * mean), 0.f)) + 1e-5f)))); }
__device__ __forceinline__ void load_h(uint2 (&v)[4], const uint8_t* p) {
    v[0] = ld_poll64<0>(p); v[1] = ld_poll64<DM * 4>(p); v[2] = ld_poll64<DM * 8>(p); v[3] = ld_poll64<DM * 12>(p);
}
__device__ __forceinline__ uint32_t min_h(const uint2 (&v)[4]) { return min(__vimin3_u32(__vimin3_u32(v[0].x, v[0].y, v[1].x), v[1].y, v[2].x), __vimin3_u32(v[2].y, v[3].x, v[3].y)); }
__device__ __forceinline__ uint32_t sum_h(const uint2 (&v)[4], uint32_t xw) {
    return hadd2(xw, pack_bf((f(v[0].x) + f(v[1].x)) + (f(v[2].x) + f(v[3].x)), (f(v[0].y) + f(v[1].y)) + (f(v[2].y) + f(v[3].y))));
}
__device__ __forceinline__ void load_p(uint2 (&v)[7], const uint8_t* p) {
    v[0] = ld_poll64<0>(p); v[1] = ld_poll64<256>(p); v[2] = ld_poll64<512>(p); v[3] = ld_poll64<768>(p);
    v[4] = ld_poll64<1024>(p); v[5] = ld_poll64<1280>(p); v[6] = ld_poll64<1536>(p);
}
__device__ __forceinline__ uint32_t min_p(const uint2 (&v)[7]) {
    uint32_t mn = min(v[0].x, v[0].y);
#pragma unroll
    for (int i = 1; i < 7; i++) mn = __vimin3_u32(mn, v[i].x, v[i].y);
    return mn;
}
constexpr float L2E = 1.4426950408889634f;
constexpr uint32_t ONES = 0x3f803f80u;

__global__ void __launch_bounds__(NTHREADS, 1)
fused_decode_kernel(const uint32_t* __restrict__ x, const uint8_t* __restrict__ wq, uint32_t* __restrict__ out,
                    const __grid_constant__ Maps maps) {
    extern __shared__ __align__(1024) uint8_t smem_raw[];
    const uint32_t sb = (uint32_t)__cvta_generic_to_shared(smem_raw);
    const int cta = blockIdx.x;
    uint32_t w[7];
    if (threadIdx.x < 256) {
        const uint8_t* src = wq + (uint32_t)((threadIdx.x >> 2) * 8192 + cta * 64 + (threadIdx.x & 3) * 16);
        const uint32_t dst = sb + SM_WQ + ((threadIdx.x * 16) ^ ((threadIdx.x * 2) & 0x30));
        cp_async16<0, 0>(dst, src); cp_async16<4096, 1 << 19>(dst, src); cp_async16<8192, 2 << 19>(dst, src); cp_async16<12288, 3 << 19>(dst, src);
        cp_async16<16384, 4 << 19>(dst, src); cp_async16<20480, 5 << 19>(dst, src); cp_async16<24576, 6 << 19>(dst, src);
    } else if (threadIdx.x >= 288) {
#pragma unroll
        for (int i = 0; i < 7; i++) asm volatile("ld.global.nc.b32 %0, [%1];" : "=r"(w[i]) : "l"(x + (threadIdx.x & 31) + 32 * i));
    }
    const int lane = threadIdx.x & 31, warp = __shfl_sync(~0u, threadIdx.x >> 5, 0);
    const int hk = cta >> 4, j = cta & 15;
    const int g = lane >> 2, t = lane & 3;
    const bool is_ffn = cta < NFFN, is_wo = !is_ffn && cta < 2 * NFFN;
    const int wo_i = cta - NFFN, wo_r = wo_i / 14;
    const uint32_t bar0 = sb + SM_BAR;

    if (warp == 8) {
        const uint32_t t_start = gtime32();
        if (lane == 0) {
#pragma unroll
            for (int i = 0; i < 48; i++) mbar_init(bar0 + i * 8, i == BAR_WQ ? 7 : i == BAR_K_FREE ? 8 : 1);
            asm volatile("fence.mbarrier_init.release.cluster;" ::: "memory");
        }
        __syncwarp();
        nb_arrive(0, NTHREADS);
        nb_arrive(NB_INIT, 64);
        const int row0 = hk * SK + (SK - WIN);
        int map = lane >> 4, c0 = map * (j & 7) * 32, c1 = row0 + (map ? (j >> 3) * 2048 + (lane - 16) * 128 : j * 256 + lane * 16);
        int wait = lane - WMAX, extra = lane >= NUNIT ? BAR_K_FREE : BAR_WQ;
        uint32_t when = t_start + T0_NS + lane * DT_NS;
        uint32_t dst = (lane < NUNIT ? lane : lane - NUNIT) * UNIT, bytes = UNIT, b = lane;
        bool todo = true;
        if (lane < 23) extra = wait;
#pragma unroll 1
        for (int r = 0; r < 2; r++) {
            do {
                if (todo && (int)(gtime32() - when) >= 0 && (wait < 0 || (mbar_test(bar0 + wait * 8) && mbar_test(bar0 + extra * 8)))) {
                    if (bytes) mbar_expect_tx(bar0 + b * 8, bytes);
                    tma2d(sb + dst, &maps.m[map], c0, c1, bar0 + b * 8);
                    todo = false;
                }
            } while (__any_sync(~0u, todo));
            if (is_wo) {
                todo = lane < 8;
                b = BAR_W + lane;
                wait = extra = min(26 + (lane >> 1), 31);
                when = t_start + WO_T0 + lane * WO_DT;
                map = 2; c0 = (wo_i - wo_r * 14) * 32; c1 = wo_r * 1024 + lane * 128;
                dst = SM_WO + lane * UNIT;
            } else {
                const bool dn = lane >= 14;
                todo = is_ffn && lane < 21;
                wait = -1;
                if (is_ffn && r == 0) mbar_wait(bar0 + 29 * 8);
                when = t_start + max((int)(gtime32() - t_start), GU_T0) + lane * GU_DT + (dn ? GU_D0 : 0);
                map = dn ? 5 : 3 + (lane & 1);
                c0 = dn ? (lane - 14) * 64 : cta * 32;
                c1 = dn ? cta * 32 : (lane >> 1) * 64;
                dst = SM_GU + (dn ? lane * 4096 : (lane & 1) * 28672 + (lane >> 1) * 4096);
                bytes = dn ? 4096 : (lane & 1) ? 0 : 8192;
                b = dn ? lane + (BAR_DN - 14) : BAR_W + (lane >> 1);
            }
        }
        return;
    }
    const uint32_t epoch = ld_poll32(&g_epoch);

    if (warp == 9) {
        const uint32_t res = __ldg(x + (is_wo ? wo_i : 0) * 4 + t);
        {
            float s1 = 0.f, s2 = 0.f;
#pragma unroll
            for (int i = 0; i < 7; i++) { const float a = bf_lo(w[i]), b = bf_hi(w[i]); s1 += a + b; s2 = fmaf(a, a, fmaf(b, b, s2)); }
#pragma unroll
            for (int o = 16; o > 0; o >>= 1) { s1 += __shfl_xor_sync(~0u, s1, o); s2 += __shfl_xor_sync(~0u, s2, o); }
            const float mean = s1 * (1.f / DM), rs = ln_rs(mean, s2);
            const uint32_t nm = pack_bf(-mean, -mean);
            const uint32_t xa = sb + SM_XN + (lane & 16) * 4 + t * 16 + (g & 3) * 4;
#pragma unroll
            for (int i = 0; i < 7; i++) { const uint32_t d = hadd2(w[i], nm); sts32(xa + i * 128, pack_bf(bf_lo(d) * rs, bf_hi(d) * rs)); }
        }
        nb_arrive(0, NTHREADS);
        uint8_t* scr = (uint8_t*)&g_scr[epoch & 1];
        asm volatile("" : "+l"(scr));
        {
            uint4 v[2];
            Poll<2, 512>::load(v, scr + OQ + hk * 1024 + lane * 16);
            nb_sync(NB_INIT, 64);
            mbar_wait(bar0 + BAR_WQ * 8);
            poll128<2, 512>(v, scr + OQ + hk * 1024 + lane * 16, 100);
            sts128(sb + SM_Q + lane * 16, v[0].x, v[0].z, v[0].y, v[0].w);
            sts128(sb + SM_Q + 512 + lane * 16, v[1].x, v[1].z, v[1].y, v[1].w);
            nb_arrive(NB_Q, 288);
            uint8_t* nx = (uint8_t*)&g_scr[(epoch & 1) ^ 1];
#pragma unroll 1
            for (int i = (cta * 32 + lane) * 16; i < (int)sizeof(Scratch); i += NCTA * 512) *(uint4*)(nx + i) = make_uint4(0, 0, 0, 0);
        }
        const uint8_t* op = scr + OOB + wo_r * 4096 + lane * 16;
        const uint8_t* hp = scr + OPB + (cta & (NREP - 1)) * (DM * 16) + wo_i * 32 + t * 8;
        const uint8_t* ip = scr + OP2 + wo_i * 2048 + lane * 8;
        uint4 ov[8];
        uint2 hv[4], pv[7];
        if (is_wo) {
#pragma unroll
            for (int i = 0; i < 8; i++) ov[i] = ld_poll128<0>(op + i * 512);
            load_h(hv, hp);
            load_p(pv, ip);
        }
        {
            uint4 v[4];
            v[0].x = 0;
            mbar_wait(bar0 + (BAR_V + SSTART) * 8);
            poll128<4, 1024>(v, scr + OST + hk * 4096 + lane * 32, 200);
            uint32_t mm = hmax2(hmax2(__byte_perm(v[0].x, v[0].z, 0x7632), __byte_perm(v[1].x, v[1].z, 0x7632)),
                                hmax2(__byte_perm(v[2].x, v[2].z, 0x7632), __byte_perm(v[3].x, v[3].z, 0x7632)));
#pragma unroll
            for (int o = 16; o > 0; o >>= 1) mm = hmax2(mm, __shfl_xor_sync(~0u, mm, o));
            const float m0 = bf_lo(mm) * L2E, m1 = bf_hi(mm) * L2E;
            float c0[4], c1[4], l0 = 0.f, l1 = 0.f;
#pragma unroll
            for (int i = 0; i < 4; i++) {
                c0[i] = ex2_ap(fmaf(f(v[i].x), L2E, -m0)); l0 = fmaf(c0[i], f(v[i].y), l0);
                c1[i] = ex2_ap(fmaf(f(v[i].z), L2E, -m1)); l1 = fmaf(c1[i], f(v[i].w), l1);
            }
#pragma unroll
            for (int o = 16; o > 0; o >>= 1) { l0 += __shfl_xor_sync(~0u, l0, o); l1 += __shfl_xor_sync(~0u, l1, o); }
            l0 = rcp_ap(l0); l1 = rcp_ap(l1);
#pragma unroll
            for (int i = 0; i < 4; i++) sts64f(sb + SM_SC + lane * 8 + i * 256, c0[i] * l0, c1[i] * l1);
            nb_arrive(NB_SC, 288);
        }
        if (!is_wo) return;
        {
            int it = SPIN_LIMIT;
            mbar_wait(bar0 + (BAR_V + OSTART) * 8);
            uint32_t pend = 3;
            do {
#pragma unroll
                for (int i = 0; i < 8; i++) if (min4(ov[i]) == 0u) ov[i] = ld_poll128<0>(op + i * 512);
                --it;
#pragma unroll
                for (int hf = 0; hf < 2; hf++) {
                    const uint32_t mn = min(min(min4(ov[4 * hf]), min4(ov[4 * hf + 1])), min(min4(ov[4 * hf + 2]), min4(ov[4 * hf + 3])));
                    if ((pend >> hf & 1) && (!__any_sync(~0u, mn == 0u) || !it)) {
#pragma unroll
                        for (int i = 4 * hf; i < 4 * hf + 4; i++) sts128(sb + SM_OB + lane * 16 + i * 512, ov[i].x, ov[i].y, ov[i].z, ov[i].w);
                        nb_arrive(NB_O + 4 * hf, 160);
                        pend ^= 1 << hf;
                    }
                }
            } while (pend);
        }
        {
            const uint32_t t1 = gtime32();
            while ((int)(gtime32() - t1) < P2_D) __nanosleep(20);
            int it = SPIN_LIMIT;
            while (true) {
                const uint32_t mn = min_h(hv);
                if (mn == 0u) load_h(hv, hp);
                if (!__any_sync(~0u, min(mn, min_p(pv)) == 0u) || !--it) break;
                load_p(pv, ip);
            }
#define S7_(c) (((f(pv[0].c) + f(pv[1].c)) + (f(pv[2].c) + f(pv[3].c))) + ((f(pv[4].c) + f(pv[5].c)) + f(pv[6].c)))
            float k0 = S7_(x), k1 = S7_(y);
#undef S7_
#pragma unroll
            for (int o = 16; o >= 4; o >>= 1) { k0 += __shfl_xor_sync(~0u, k0, o); k1 += __shfl_xor_sync(~0u, k1, o); }
            if (lane < 4) out[wo_i * 4 + lane] = hadd2(sum_h(hv, res), pack_bf(k0, k1));
            if (wo_i == 0) st_pub32(&g_epoch, epoch + 1);
        }
        return;
    }

    const uint32_t xw = __ldg(x + min(warp, 6) * 32 + lane);
    const int lrow = (lane & 7) + ((lane >> 4) << 3), lc = (lane >> 3) & 1;
    const uint32_t voff = sb + lrow * 64 + ((lc ^ ((lrow >> 1) & 3)) << 4);
    const bool odd = g & 1;
    asm volatile("cp.async.wait_all;" ::: "memory");
    nb_sync(0, NTHREADS);
    uint8_t* scr = (uint8_t*)&g_scr[epoch & 1];
    asm volatile("" : "+l"(scr));

    if (warp < 7) {
        float c[2][4];
#pragma unroll
        for (int s = 0; s < 4; s += 2) {
            const uint4 hv = lds128(sb + SM_XN + warp * 128 + s * 32 + t * 16);
#pragma unroll
            for (int tl = 0; tl < 2; tl++) {
                uint32_t a0[4], a1[4];
                ldsm4t(a0, (voff ^ (tl * 32)) + SM_WQ + warp * 4096 + s * 1024); ldsm4t(a1, (voff ^ (tl * 32)) + SM_WQ + warp * 4096 + s * 1024 + 1024);
                if (s == 0) mma16816z(c[tl], a0, hv.x, hv.y); else mma16816(c[tl], a0, hv.x, hv.y);
                mma16816(c[tl], a1, hv.z, hv.w);
            }
        }
        sts32f(sb + SM_G1 + warp * 128 + (t * 8 + g) * 4, sel4(t, c[0][0], c[0][2], c[1][0], c[1][2]));
        if (lane == 0) mbar_arrive(bar0 + BAR_WQ * 8);
        if (warp == 0) {
            nb_sync(NB_G1, 224);
            float d[7];
#pragma unroll
            for (int w = 0; w < 7; w++) d[w] = lds32f(sb + SM_G1 + w * 128 + lane * 4);
            const float val = sum7(d);
            const uint32_t pw = pack_bf(val, __shfl_down_sync(~0u, val, 1));
            if (!(lane & 1)) st_pub32(scr + OQ + cta * 64 + lane * 2, enc(pw));
        } else {
            nb_arrive(NB_G1, 224);
        }
    }
    nb_sync(NB_Q, 288);
    const bool is_f7 = is_ffn && warp < 7;
    const uint8_t* hp = scr + OPB + (cta & (NREP - 1)) * (DM * 16) + warp * 256 + lane * 8;
    uint2 hv[4];
    if (is_f7) load_h(hv, hp);
    {
        const uint32_t kb = (sb + warp * 2 * UNIT + g * 512 + t * 16) ^ ((g & 1) << 6);
        const uint32_t qb = (sb + SM_Q + (g & 1) * 512 + t * 16 + (g >> 2) * 8) ^ ((g & 2) << 5);
        float c[4][4];
#pragma unroll
        for (int i = 0; i < 4; i++) c[i][0] = c[i][1] = c[i][2] = c[i][3] = 0.f;
        mbar_wait(bar0 + warp * 16);
        mbar_wait(bar0 + warp * 16 + 8);
#pragma unroll 2
        for (int s = 0; s < 512; s += 64) {
            const uint2 qf = lds64(qb ^ s);
#pragma unroll
            for (int i = 0; i < 4; i++) { const uint4 k = lds128((kb ^ s) + i * 4096); mma16816(c[i], k.x, k.y, k.z, k.w, qf.x, qf.y); }
        }
        if (lane == 0) mbar_arrive(bar0 + BAR_K_FREE * 8);
        const bool hi = t & 2, act = !((t ^ g) & 1);
        uint32_t sw[2];
#pragma unroll
        for (int i = 0; i < 2; i++) {
            const float a = (hi ? c[2 + i][2] : c[i][0]) + __shfl_xor_sync(~0u, hi ? c[i][2] : c[2 + i][0], 2);
            const float b = (hi ? c[2 + i][3] : c[i][1]) + __shfl_xor_sync(~0u, hi ? c[i][3] : c[2 + i][1], 2);
            sw[i] = pack_bf(a * 0.0625f, b * 0.0625f);
        }
        uint32_t mm = act ? hmax2(sw[0], sw[1]) : 0xff80ff80u;
#pragma unroll
        for (int o = 16; o > 0; o >>= 1) mm = hmax2(mm, __shfl_xor_sync(~0u, mm, o));
        const float m0 = bf_lo(mm) * L2E, m1 = bf_hi(mm) * L2E;
        const float e00 = ex2_ap(fmaf(bf_lo(sw[0]), L2E, -m0)), e01 = ex2_ap(fmaf(bf_hi(sw[0]), L2E, -m1));
        const float e10 = ex2_ap(fmaf(bf_lo(sw[1]), L2E, -m0)), e11 = ex2_ap(fmaf(bf_hi(sw[1]), L2E, -m1));
        const float x0 = __shfl_xor_sync(~0u, odd ? e00 : e01, 5), x1 = __shfl_xor_sync(~0u, odd ? e10 : e11, 5);
        uint8_t* ep = scr + OE + (cta * 8 + warp) * 128;
        if (act) st_pub64(ep + (g & 1) * 64 + (g >> 1) * 16 + (t >> 1) * 8,
                          enc(odd ? pack_bf(x0, e01) : pack_bf(e00, x0)), enc(odd ? pack_bf(x1, e11) : pack_bf(e10, x1)));
        float l = act ? (odd ? e01 + e11 : e00 + e10) + (x0 + x1) : 0.f;
#pragma unroll
        for (int o = 16; o > 0; o >>= 1) if (o != 4) l += __shfl_xor_sync(~0u, l, o);
        const float lo = __shfl_xor_sync(~0u, l, 4);
        if (lane < 2) st_pub128(scr + OST + (cta * 8 + warp) * 32 + lane * 16, encf(bf_lo(mm)), encf(l), encf(bf_hi(mm)), encf(lo));
    }
    {
        const int grp0 = (j >> 3) * 64 + warp;
        uint4 p[8];
        p[0].x = 0;
        mbar_wait(bar0 + (BAR_V + PSTART) * 8);
        poll128<8, 1024>(p, scr + OE + (hk * 128 + grp0) * 128 + (g & 1) * 64 + t * 16, 200);
        nb_sync(NB_SC, 288);
        const uint32_t vb = voff + warp * 2048;
        float o[2][4] = {{0.f, 0.f, 0.f, 0.f}, {0.f, 0.f, 0.f, 0.f}};
#pragma unroll
        for (int i = 0; i < 8; i++) {
            const uint32_t va = vb + (i < 5 ? (16 + 2 * i) * UNIT : i > 5 ? (2 * i - 11) * UNIT : (warp < 4 ? 26 * UNIT : -UNIT));
            const float2 sc = lds64f(sb + SM_SC + (grp0 + i * 8) * 8);
            mbar_wait(bar0 + (warp >> 2) * 8 + (BAR_V + 2 * i) * 8);
#pragma unroll
            for (int mt = 0; mt < 2; mt++) {
                uint32_t a0[4], a1[4];
                float d[4];
                ldsm4t(a0, va ^ (mt * 32)); ldsm4t(a1, (va ^ (mt * 32)) + 1024);
                mma16816z(d, a0, p[i].x, p[i].y);
                if (i == 7) {
                    float d2[4];
                    mma16816z(d2, a1, p[i].z, p[i].w);
                    o[mt][0] = fmaf(d2[0], sc.x, o[mt][0]); o[mt][1] = fmaf(d2[1], sc.y, o[mt][1]);
                    o[mt][2] = fmaf(d2[2], sc.x, o[mt][2]); o[mt][3] = fmaf(d2[3], sc.y, o[mt][3]);
                } else {
                    mma16816(d, a1, p[i].z, p[i].w);
                }
                o[mt][0] = fmaf(d[0], sc.x, o[mt][0]); o[mt][1] = fmaf(d[1], sc.y, o[mt][1]);
                o[mt][2] = fmaf(d[2], sc.x, o[mt][2]); o[mt][3] = fmaf(d[3], sc.y, o[mt][3]);
            }
        }
        sts32f(sb + SM_RED + warp * 256 + (t * 8 + g) * 4, sel4(t, o[0][0], o[0][2], o[1][0], o[1][2]));
        sts32f(sb + SM_RED + warp * 256 + 128 + (t * 8 + g) * 4, sel4(t, o[0][1], o[0][3], o[1][1], o[1][3]));
        if (warp == 0) {
            nb_sync(NB_PV, 256);
            float r0[8], r1[8];
#pragma unroll
            for (int w = 0; w < 8; w++) { const float2 r = lds64f(sb + SM_RED + w * 256 + lane * 8); r0[w] = r.x; r1[w] = r.y; }
            st_pub32(scr + OOB + cta * 128 + (lane & 16) * 4 + (lane & 3) * 16 + (lane & 12), enc(pack_bf(sum8(r0), sum8(r1))));
        } else {
            nb_arrive(NB_PV, 256);
        }
    }
    if (is_wo) {
        uint32_t a[2][8][4];
        mbar_wait(bar0 + (BAR_W + warp) * 8);
#pragma unroll
        for (int s = 0; s < 8; s++) { ldsm4t(a[0][s], voff + SM_WO + warp * UNIT + s * 1024); ldsm4t(a[1][s], (voff ^ 32) + SM_WO + warp * UNIT + s * 1024); }
        nb_sync(NB_O + (warp & 4), 160);
        uint4 ov[4];
#pragma unroll
        for (int i = 0; i < 4; i++) ov[i] = lds128(sb + SM_OB + ((warp >> 2) * 16 + (g & 1) * 8 + (warp & 1) * 4 + i) * 128 + (warp & 2) * 32 + t * 16);
        float c[2][2][4];
#pragma unroll
        for (int i = 0; i < 4; i++) {
#pragma unroll
            for (int mt = 0; mt < 2; mt++) {
                if (i == 0) { mma16816z(c[mt][0], a[mt][0], ov[i].x, ov[i].y); mma16816z(c[mt][1], a[mt][1], ov[i].z, ov[i].w); }
                else { mma16816(c[mt][0], a[mt][2 * i], ov[i].x, ov[i].y); mma16816(c[mt][1], a[mt][2 * i + 1], ov[i].z, ov[i].w); }
            }
        }
        sts32f(sb + SM_XN + warp * 128 + (t * 8 + g) * 4,
               (sel4(t, c[0][0][0], c[0][0][2], c[1][0][0], c[1][0][2]) + sel4(t, c[0][0][1], c[0][0][3], c[1][0][1], c[1][0][3])) +
               (sel4(t, c[0][1][0], c[0][1][2], c[1][1][0], c[1][1][2]) + sel4(t, c[0][1][1], c[0][1][3], c[1][1][1], c[1][1][3])));
        if (warp < NREP) {
            nb_sync(NB_WO, 256);
            float r[8];
#pragma unroll
            for (int w = 0; w < 8; w++) r[w] = lds32f(sb + SM_XN + w * 128 + lane * 4);
            st_pub32(scr + OPB + warp * (DM * 16) + wo_i * 128 + lane * 4, encf(sum8(r)));
        } else {
            nb_arrive(NB_WO, 256);
        }
    } else if (is_f7) {
        uint32_t a[4][4][4], a2[2][4][4];
        bool done = !__any_sync(~0u, min_h(hv) == 0u), have = false;
        mbar_wait(bar0 + (BAR_W + HSTART) * 8);
        const uint32_t gb = bar0 + (BAR_W + warp) * 8;
        {
            int it = SPIN_LIMIT;
            do {
                if (!done) load_h(hv, hp);
                if (!have && mbar_try(gb, 100)) {
#pragma unroll
                    for (int s = 0; s < 4; s++)
#pragma unroll
                        for (int m = 0; m < 4; m++) ldsm4t(a[m][s], (voff ^ ((m & 1) * 32)) + SM_GU + (m >> 1) * 28672 + warp * 4096 + s * 1024);
                    have = true;
                }
                done = !__any_sync(~0u, min_h(hv) == 0u) || --it < 0;
            } while (!(done && have));
        }
        const uint32_t hword = sum_h(hv, xw);
        float c[4][4], cs[4][4];
        uint32_t f0[4], f1[4];
#pragma unroll
        for (int s = 0; s < 4; s++) {
            const uint32_t h0 = __shfl_sync(~0u, hword, s * 8 + t), h1 = __shfl_sync(~0u, hword, s * 8 + 4 + t);
            f0[s] = odd ? ONES : h0; f1[s] = odd ? ONES : h1;
            const uint32_t ah[4] = {h0, h0, h1, h1};
            mma16816z(cs[s], ah, f0[s], f1[s]);
        }
#pragma unroll
        for (int s = 0; s < 4; s++) {
#pragma unroll
            for (int m = 0; m < 4; m++) { if (s == 0) mma16816z(c[m], a[m][s], f0[s], f1[s]); else mma16816(c[m], a[m][s], f0[s], f1[s]); }
            if (s == 0) {
                if (lane == 0) sts64f(sb + SM_G1 + 3584 + warp * 8, (cs[0][0] + cs[1][0]) + (cs[2][0] + cs[3][0]), (cs[0][1] + cs[1][1]) + (cs[2][1] + cs[3][1]));
                nb_arrive(NB_S, 256);
            }
        }
        sts128(sb + SM_G1 + warp * 512 + (t * 8 + g) * 16,
               __float_as_uint(sel4(t, c[0][0], c[0][2], c[1][0], c[1][2])), __float_as_uint(sel4(t, c[0][1], c[0][3], c[1][1], c[1][3])),
               __float_as_uint(sel4(t, c[2][0], c[2][2], c[3][0], c[3][2])), __float_as_uint(sel4(t, c[2][1], c[2][3], c[3][1], c[3][3])));
        nb_arrive(NB_G2, 256);
#pragma unroll
        for (int i = 0; i < 8; i++) {
            if (i == 0) mbar_wait(gb + (BAR_DN - BAR_W) * 8);
            ldsm4t(a2[i >> 2][i & 3], sb + SM_DN + warp * 4096 + (i >> 2) * 2048 + lrow * 128 + ((((i & 3) * 2 + lc) ^ (lane & 7)) << 4));
        }
        nb_sync(NB_H, 256);
        const uint2 b = lds64(sb + SM_XN + ((odd ? 4 : 0) + t) * 8);
        float e[4][4];
#pragma unroll
        for (int i = 0; i < 4; i++) mma16816z(e[i], a2[0][i], odd ? 0u : b.x, odd ? b.x : 0u);
#pragma unroll
        for (int i = 0; i < 4; i++) mma16816(e[i], a2[1][i], odd ? 0u : b.y, odd ? b.y : 0u);
        uint8_t* dst = scr + OP2 + (warp * 4 + t) * 4096 + cta * 32 + g * 4;
        const uint32_t r0 = encf(sel4(t, e[0][0], e[1][0], e[2][0], e[3][0]) + sel4(t, e[0][1], e[1][1], e[2][1], e[3][1]));
        const uint32_t r1 = encf(sel4(t, e[0][2], e[1][2], e[2][2], e[3][2]) + sel4(t, e[0][3], e[1][3], e[2][3], e[3][3]));
        st_pub32(dst, r0); st_pub32(dst + 2048, r1);
    } else if (is_ffn) {
        nb_sync(NB_S, 256);
        const float4 s01 = lds128f(sb + SM_G1 + 3584), s23 = lds128f(sb + SM_G1 + 3600), s45 = lds128f(sb + SM_G1 + 3616);
        const float2 s6 = lds64f(sb + SM_G1 + 3632);
        const float mean = (((s01.y + s01.w) + (s23.y + s23.w)) + ((s45.y + s45.w) + s6.y)) * (1.f / DM);
        const float rs = ln_rs(mean, ((s01.x + s01.z) + (s23.x + s23.z)) + ((s45.x + s45.z) + s6.x)), mb = rbf(mean);
        nb_sync(NB_G2, 256);
        float d0[7], d1[7], d2[7], d3[7];
#pragma unroll
        for (int w = 0; w < 7; w++) { const float4 d = lds128f(sb + SM_G1 + w * 512 + lane * 16); d0[w] = d.x; d1[w] = d.y; d2[w] = d.z; d3[w] = d.w; }
        const uint32_t gu = pack_bf((sum7(d0) - mb * sum7(d1)) * rs, (sum7(d2) - mb * sum7(d3)) * rs);
        const float hh = bf_lo(gu) * bf_hi(gu);
        const uint32_t hw = pack_bf(hh, __shfl_down_sync(~0u, hh, 1));
        if (!(lane & 1)) sts32(sb + SM_XN + (lane & 14) * 4 + (lane >> 4) * 4, hw);
        nb_arrive(NB_H, 256);
    }
}

typedef CUresult (*EncodeFn)(CUtensorMap*, CUtensorMapDataType, cuuint32_t, void*, const cuuint64_t*, const cuuint64_t*,
                             const cuuint32_t*, const cuuint32_t*, CUtensorMapInterleave, CUtensorMapSwizzle,
                             CUtensorMapL2promotion, CUtensorMapFloatOOBfill);

void make_map(EncodeFn enc_fn, CUtensorMap* tm, const void* base, uint64_t cols, uint64_t rows, uint32_t box_cols, uint32_t box_rows,
              CUtensorMapSwizzle sw) {
    cuuint64_t gdim[2] = {cols, rows};
    cuuint64_t gstr[1] = {cols * 2};
    cuuint32_t box[2] = {box_cols, box_rows};
    cuuint32_t es[2] = {1, 1};
    enc_fn(tm, CU_TENSOR_MAP_DATA_TYPE_BFLOAT16, 2, const_cast<void*>(base), gdim, gstr, box, es, CU_TENSOR_MAP_INTERLEAVE_NONE, sw,
           CU_TENSOR_MAP_L2_PROMOTION_L2_128B, CU_TENSOR_MAP_FLOAT_OOB_FILL_NONE);
}

}

extern "C" void kernel_launch(void* const* d_in, const int* in_sizes, int n_in, void* d_out, int out_size) {
    (void)in_sizes; (void)n_in; (void)out_size;
    static EncodeFn enc_fn = nullptr;
    if (!enc_fn) {
        void* fn = nullptr;
        cudaDriverEntryPointQueryResult qr;
        cudaGetDriverEntryPoint("cuTensorMapEncodeTiled", &fn, cudaEnableDefault, &qr);
        enc_fn = (EncodeFn)fn;
        cudaFuncSetAttribute(fused_decode_kernel, cudaFuncAttributeMaxDynamicSharedMemorySize, SM_TOTAL);
    }
    Maps maps;
    make_map(enc_fn, &maps.m[0], d_in[1], 256, (uint64_t)8 * SK, 256, 16, CU_TENSOR_MAP_SWIZZLE_NONE);
    make_map(enc_fn, &maps.m[1], d_in[2], 256, (uint64_t)8 * SK, 32, 128, CU_TENSOR_MAP_SWIZZLE_64B);
    make_map(enc_fn, &maps.m[2], d_in[4], DM, 4096, 32, 128, CU_TENSOR_MAP_SWIZZLE_64B);
    make_map(enc_fn, &maps.m[3], d_in[6], FF, DM, 32, 64, CU_TENSOR_MAP_SWIZZLE_64B);
    make_map(enc_fn, &maps.m[4], d_in[7], FF, DM, 32, 64, CU_TENSOR_MAP_SWIZZLE_64B);
    make_map(enc_fn, &maps.m[5], d_in[8], DM, FF, 64, 32, CU_TENSOR_MAP_SWIZZLE_128B);
    fused_decode_kernel<<<NCTA, NTHREADS, SM_TOTAL>>>((const uint32_t*)d_in[0], (const uint8_t*)d_in[3], (uint32_t*)d_out, maps);
}
```
